```python
import torch

def _softmax(x, axis=-1):
    return torch.softmax(x, dim=axis)
def _gelu(x):
    return torch.nn.functional.gelu(x, approximate="tanh")
def _silu(x):
    return torch.nn.functional.silu(x)
def _sigmoid(x):
    return torch.sigmoid(x)
def _layernorm(x, axis=-1, eps=1e-5):
    m = x.mean(dim=axis, keepdim=True)
    v = x.var(dim=axis, keepdim=True, unbiased=False)
    return (x - m) / torch.sqrt(v + eps)
def _scatter_add(tgt, idx, src, axis=0):
    return tgt.clone().index_add_(axis, idx, src)
def _segment_sum(src, seg, n):
    out = torch.zeros((n,) + src.shape[1:], dtype=src.dtype)
    return out.index_add_(0, seg, src)
def _pad(x, pw):
    flat = tuple(v for pair in reversed(pw) for v in pair)
    return torch.nn.functional.pad(x, flat)

kernel_name = 'recurrent_scan__spectral_gfnet__mixer_s_mlp__prompt'

def setup_inputs():

    _w = (lambda a: (lambda t: t.to(torch.bfloat16) if t.is_floating_point() else t)(torch.as_tensor(a)))
    def _A_setup():
        B, S, D = 1, 2048, 640
        Df = D // 2 + 1
        return {
            "x": _w((lambda *s: torch.randn(*s, dtype=torch.bfloat16) * 0.05)(B, S, D)),
            "w_r": _w((lambda *s: torch.randn(*s, dtype=torch.bfloat16) * 0.2)(S, Df) * 0.02),
            "w_i": _w((lambda *s: torch.randn(*s, dtype=torch.bfloat16) * 0.2)(S, Df) * 0.02),
        }
    _A_in = _A_setup()

    def _B_setup():
        B, S, D, F = 1, 2048, 640, 1536
        return {
            "x":  _w((lambda *s: torch.randn(*s, dtype=torch.bfloat16) * 0.05)(B, S, D)),
            "w1": _w((lambda *s: torch.randn(*s, dtype=torch.bfloat16) * 1.6)(D, D) * (D ** -0.5)),
            "w2": _w((lambda *s: torch.randn(*s, dtype=torch.bfloat16) * 1.6)(D, D) * (D ** -0.5)),
            "w3": _w((lambda *s: torch.randn(*s, dtype=torch.bfloat16) * 1.6)(D, F) * (D ** -0.5)),
            "w4": _w((lambda *s: torch.randn(*s, dtype=torch.bfloat16) * 1.6)(F, D) * (F ** -0.5)),
        }
    _B_in = _B_setup()

    return {
        "A_x": _A_in["x"],
        "A_w_r": _A_in["w_r"],
        "A_w_i": _A_in["w_i"],
        "B_x": _B_in["x"],
        "B_w1": _B_in["w1"],
        "B_w2": _B_in["w2"],
        "B_w3": _B_in["w3"],
        "B_w4": _B_in["w4"],
    }

def reference(A_x, A_w_r, A_w_i, B_x, B_w1, B_w2, B_w3, B_w4):
    def _A_ref(x, w_r, w_i):
        B, S, D = x.shape
        X = (lambda x, axes=(-2,-1): torch.fft.rfft2(x.float(), dim=axes))(x, axes=(-2, -1))
        W = w_r + 1j * w_i
        X = X * W
        y = (lambda x, s, axes=(-2,-1): torch.fft.irfft2(x, s=s, dim=axes).to(torch.bfloat16))(X, (S, D), axes=(-2, -1))
        return y

    def _B_ref(x, w1, w2, w3, w4):
        B, S, D = x.shape
        h = _gelu(_layernorm(x, axis=-1) @ w1)
        c = D // 4
        g0 = _pad(h[:, :, 0*c:1*c], ((0, 0), (1, 0), (0, 0)))[:, :S, :]
        g1 = _pad(h[:, :, 1*c:2*c], ((0, 0), (0, 1), (0, 0)))[:, 1:, :]
        g2 = _pad(h[:, :, 2*c:3*c], ((0, 0), (2, 0), (0, 0)))[:, :S, :]
        g3 = _pad(h[:, :, 3*c:   ], ((0, 0), (0, 2), (0, 0)))[:, 2:, :]
        hs = torch.concatenate([g0, g1, g2, g3], axis=-1) @ w2
        x1 = x + hs
        h2 = _gelu(_layernorm(x1, axis=-1) @ w3) @ w4
        return x1 + h2

    x = A_x
    xn = _layernorm(x, axis=-1)
    s = _A_ref(xn, A_w_r, A_w_i)
    g = _silu(_B_ref(xn, B_w1, B_w2, B_w3, B_w4))
    return x + s * g
```

```cpp
#include <cuda_runtime.h>
#include <cuda_bf16.h>
#include <cuda.h>
#include <stdint.h>

#define DEVI __device__ __forceinline__

struct __align__(1024) Scratch {
  unsigned char tab[2 * 409600];
  unsigned char rem[34 * 16384];
  unsigned char h[32 * 20 * 4096];
  unsigned char x1[32 * 20 * 4096];
  unsigned char h2[32 * 48 * 4096];
  unsigned char Y[32 * 10 * 8192];
  __nv_bfloat16 T1[2048 * 640];
  __nv_bfloat16 T2[2048 * 640];
  float2 st1[32 * 8 * 64];
  float cs1[4 * 640];
  float cs3[4 * 1536];
  float4 row[2048];
  unsigned int flag[128 * 32];
  unsigned int epoch[160];
};
__device__ Scratch g_sc;

enum { F_H = 0, F_X1 = 8, F_H2 = 24, F_Y = 48, F_TAB = 80, F_W2 = 81, F_W4 = 82, F_T1 = 83, F_T2 = 85, F_CS3 = 88 };

enum : uint32_t {
  NST = 6, SLOT = 28672, NPRE = 2,
  G5AT = 12,
  SM = 1024,
  STG = SM + NST * SLOT,
  FB = STG + 20480,
  BAR = FB + 24576,
  ROW = BAR + 256,
  CS1 = ROW + 1024,
  CS3 = CS1 + 640,
  ST1 = CS3 + 768,
  CSP = ST1 + 1024,
  EPO = CSP + 4352,
  PRF = EPO + 16,
  HTB = SM + 204800,
  SMEM_BYTES = PRF + 96 * 4 - SM,
  B_FM = BAR, B_FF = BAR + 48, B_EM = BAR + 96, B_G1 = BAR + 144, B_FFT = BAR + 152, B_ROW = BAR + 160, B_EP = BAR + 168, B_CS = BAR + 176, NBAR = 23,
  H128 = 0x40000040u,
  H64 = 0x80000020u,
  SL16 = SLOT >> 4
};
enum { NB_WG2 = 1, NB_INIT = 2, NB_STATS = 3, NB_S = 4, NB_RDY = 5, NB_FREE = 6, NB_CS3 = 7, NB_GO = 8, NB_DMA = 9 };
__host__ __device__ constexpr uint32_t dlo(uint32_t addr, uint32_t lbo) { return (addr >> 4) | ((lbo >> 4) << 16); }

struct Params {
  Scratch* sc;
  const __nv_bfloat16 *px, *pwr, *pwi, *pw1, *pw2, *pw3, *pw4;
  CUtensorMap x, w1a, w1b, wr, wi, w3, t1a, t1h, t1l, t2s, t2l, outa, outr, xa, xr, w2a, w4a, w2h, w4h;
};

#define SPIN_MAX 4000000
DEVI void mbar_init(uint32_t b, int c) { asm volatile("mbarrier.init.shared::cta.b64 [%0], %1;" ::"r"(b), "r"(c)); }
DEVI void mbar_expect(uint32_t b, int bytes) { asm volatile("mbarrier.arrive.expect_tx.shared::cta.b64 _, [%0], %1;" ::"r"(b), "r"(bytes) : "memory"); }
DEVI void mbar_arrive(uint32_t b) { asm volatile("mbarrier.arrive.shared::cta.b64 _, [%0];" ::"r"(b) : "memory"); }
DEVI void mbar_arrive_n(uint32_t b, uint32_t n) { asm volatile("mbarrier.arrive.shared::cta.b64 _, [%0], %1;" ::"r"(b), "r"(n) : "memory"); }
DEVI void mbar_wait(uint32_t b, uint32_t par) {
  asm volatile("{\n.reg .pred p;\n.reg .u32 c;\nmov.u32 c, 0;\nL_%=:\nmbarrier.try_wait.parity.shared::cta.b64 p, [%0], %1;\n@p bra D_%=;\n"
               "add.u32 c, c, 1;\nsetp.lt.u32 p, c, 4000000;\n@p bra L_%=;\ntrap;\nD_%=:\n}" ::"r"(b), "r"(par) : "memory");
}
DEVI bool elect() { uint32_t p; asm volatile("{\n.reg .pred P;\nelect.sync _|P, 0xffffffff;\nselp.u32 %0,1,0,P;\n}" : "=r"(p)); return p; }
DEVI void nb_sync(int id, int n) { asm volatile("bar.sync %0, %1;" ::"r"(id), "r"(n) : "memory"); }
DEVI void nb_arrive(int id, int n) { asm volatile("bar.arrive %0, %1;" ::"r"(id), "r"(n) : "memory"); }
DEVI void fence_async_smem() { asm volatile("fence.proxy.async.shared::cta;" ::: "memory"); }
DEVI void fence_async_gmem() { asm volatile("fence.proxy.async.global;" ::: "memory"); }
DEVI void bulk_ld(uint32_t dst, const void* src, int bytes, uint32_t bar) {
  asm volatile("cp.async.bulk.shared::cluster.global.mbarrier::complete_tx::bytes [%0], [%1], %2, [%3];" ::"r"(dst), "l"(src), "r"(bytes), "r"(bar) : "memory");
}
DEVI void bulk_st(void* dst, uint32_t src, int bytes) {
  asm volatile("cp.async.bulk.global.shared::cta.bulk_group [%0], [%1], %2;" ::"l"(dst), "r"(src), "r"(bytes) : "memory");
}
DEVI void tma_ld2(uint32_t dst, const CUtensorMap* m, uint32_t bar, int c0, int c1) {
  asm volatile("cp.async.bulk.tensor.2d.shared::cluster.global.mbarrier::complete_tx::bytes [%0], [%1, {%3, %4}], [%2];" ::"r"(dst), "l"(m), "r"(bar), "r"(c0), "r"(c1) : "memory");
}
DEVI void tma_ld3(uint32_t dst, const CUtensorMap* m, uint32_t bar, int c0, int c1, int c2) {
  asm volatile("cp.async.bulk.tensor.3d.shared::cluster.global.mbarrier::complete_tx::bytes [%0], [%1, {%3, %4, %5}], [%2];" ::"r"(dst), "l"(m), "r"(bar), "r"(c0), "r"(c1), "r"(c2) : "memory");
}
DEVI void tma_ld4(uint32_t dst, const CUtensorMap* m, uint32_t bar, int c0, int c1, int c2, int c3) {
  asm volatile("cp.async.bulk.tensor.4d.shared::cluster.global.mbarrier::complete_tx::bytes [%0], [%1, {%3, %4, %5, %6}], [%2];" ::"r"(dst), "l"(m), "r"(bar), "r"(c0), "r"(c1), "r"(c2), "r"(c3) : "memory");
}
DEVI void tma_st4(const CUtensorMap* m, uint32_t src, int c0, int c1, int c2, int c3) {
  asm volatile("cp.async.bulk.tensor.4d.global.shared::cta.bulk_group [%0, {%2, %3, %4, %5}], [%1];" ::"l"(m), "r"(src), "r"(c0), "r"(c1), "r"(c2), "r"(c3) : "memory");
}
DEVI void tmap_pf(const CUtensorMap* m) { asm volatile("prefetch.tensormap [%0];" ::"l"(m) : "memory"); }
DEVI void bulk_commit() { asm volatile("cp.async.bulk.commit_group;" ::: "memory"); }
DEVI void bulk_wait_read() { asm volatile("cp.async.bulk.wait_group.read 0;" ::: "memory"); }
DEVI void bulk_wait_all() { asm volatile("cp.async.bulk.wait_group 0;" ::: "memory"); }
DEVI void flag_add(Scratch* sc, int f) { asm volatile("red.relaxed.gpu.global.add.u32 [%0], 1;" ::"l"(&sc->flag[f * 32]) : "memory"); }
DEVI void flag_wait(Scratch* sc, int f, uint32_t target) {
  const unsigned int* p = &sc->flag[f * 32];
#pragma unroll 1
  for (int i = 0; i < SPIN_MAX; i++) {
    uint32_t v;
    asm volatile("ld.relaxed.gpu.global.u32 %0, [%1];" : "=r"(v) : "l"(p) : "memory");
    if ((int)(v - target) >= 0) { fence_async_gmem(); return; }
  }
  __trap();
}
DEVI void wg_fence() { asm volatile("wgmma.fence.sync.aligned;" ::: "memory"); }
DEVI void wg_commit() { asm volatile("wgmma.commit_group.sync.aligned;" ::: "memory"); }
template <int N> DEVI void wg_wait() { asm volatile("wgmma.wait_group.sync.aligned %0;" ::"n"(N) : "memory"); }
DEVI void stsm4(uint32_t a, uint32_t r0, uint32_t r1, uint32_t r2, uint32_t r3) {
  asm volatile("stmatrix.sync.aligned.m8n8.x4.shared.b16 [%0], {%1,%2,%3,%4};" ::"r"(a), "r"(r0), "r"(r1), "r"(r2), "r"(r3) : "memory");
}
DEVI void ldsm4(uint32_t a, uint32_t& r0, uint32_t& r1, uint32_t& r2, uint32_t& r3) {
  asm volatile("ldmatrix.sync.aligned.m8n8.x4.shared.b16 {%0,%1,%2,%3}, [%4];" : "=r"(r0), "=r"(r1), "=r"(r2), "=r"(r3) : "r"(a) : "memory");
}
DEVI uint32_t pack2(float lo, float hi) { uint32_t r; asm("cvt.rn.bf16x2.f32 %0, %1, %2;" : "=r"(r) : "f"(hi), "f"(lo)); return r; }
DEVI float bf_lo(uint32_t v) { return __uint_as_float(v << 16); }
DEVI float bf_hi(uint32_t v) { return __uint_as_float(v & 0xffff0000u); }
DEVI float2 lds_f2(uint32_t a) { float2 v; asm volatile("ld.shared.v2.f32 {%0,%1}, [%2];" : "=f"(v.x), "=f"(v.y) : "r"(a)); return v; }
DEVI float4 lds_f4(uint32_t a) { float4 v; asm volatile("ld.shared.v4.f32 {%0,%1,%2,%3}, [%4];" : "=f"(v.x), "=f"(v.y), "=f"(v.z), "=f"(v.w) : "r"(a)); return v; }
DEVI uint4 lds_u4(uint32_t a) { uint4 v; asm volatile("ld.shared.v4.u32 {%0,%1,%2,%3}, [%4];" : "=r"(v.x), "=r"(v.y), "=r"(v.z), "=r"(v.w) : "r"(a)); return v; }
DEVI uint32_t lds_u32(uint32_t a) { uint32_t v; asm volatile("ld.shared.u32 %0, [%1];" : "=r"(v) : "r"(a)); return v; }
DEVI void sts_u32(uint32_t a, uint32_t v) { asm volatile("st.shared.u32 [%0], %1;" ::"r"(a), "r"(v) : "memory"); }
DEVI void sts_f2(uint32_t a, float x, float y) { asm volatile("st.shared.v2.f32 [%0], {%1,%2};" ::"r"(a), "f"(x), "f"(y) : "memory"); }
DEVI void sts_f4(uint32_t a, float x, float y, float z, float w) { asm volatile("st.shared.v4.f32 [%0], {%1,%2,%3,%4};" ::"r"(a), "f"(x), "f"(y), "f"(z), "f"(w) : "memory"); }
DEVI void sts_u4(uint32_t a, uint32_t x, uint32_t y, uint32_t z, uint32_t w) { asm volatile("st.shared.v4.u32 [%0], {%1,%2,%3,%4};" ::"r"(a), "r"(x), "r"(y), "r"(z), "r"(w) : "memory"); }
DEVI uint32_t ldg_u32(const void* p) { uint32_t v; asm volatile("ld.global.u32 %0, [%1];" : "=r"(v) : "l"(p)); return v; }
DEVI uint32_t ldg_nc_u32(const void* p) { uint32_t v; asm volatile("ld.global.nc.u32 %0, [%1];" : "=r"(v) : "l"(p)); return v; }
DEVI uint32_t ldg_nc_u16(const void* p) { uint32_t v; asm volatile("ld.global.nc.u16 %0, [%1];" : "=r"(v) : "l"(p)); return v; }
DEVI uint4 ldg_nc_u4(const void* p) { uint4 v; asm volatile("ld.global.nc.v4.u32 {%0,%1,%2,%3}, [%4];" : "=r"(v.x), "=r"(v.y), "=r"(v.z), "=r"(v.w) : "l"(p)); return v; }
DEVI uint2 ldg_nc_u2(const void* p) { uint2 v; asm volatile("ld.global.nc.v2.u32 {%0,%1}, [%2];" : "=r"(v.x), "=r"(v.y) : "l"(p)); return v; }
DEVI float2 ldg_cg_f2(const void* p) { float2 v; asm volatile("ld.global.cg.v2.f32 {%0,%1}, [%2];" : "=f"(v.x), "=f"(v.y) : "l"(p)); return v; }
DEVI float tanh_fast(float x) { float y; asm("tanh.approx.f32 %0, %1;" : "=f"(y) : "f"(x)); return y; }
DEVI float silu(float v) { float hv = 0.5f * v; return fmaf(hv, tanh_fast(hv), hv); }

template <int N> DEVI void zero(float (&a)[N]) {
#pragma unroll
  for (int i = 0; i < N; i++) a[i] = 0.f;
}
template <int N> DEVI void pin(float (&a)[N]) {
#pragma unroll
  for (int i = 0; i < N; i++) asm volatile("" : "+f"(a[i])::"memory");
}
DEVI void pin1(uint32_t& v) { asm volatile("" : "+r"(v)::"memory"); }
DEVI uint32_t hadd2(uint32_t a, uint32_t b) { uint32_t r; asm("add.rn.bf16x2 %0, %1, %2;" : "=r"(r) : "r"(a), "r"(b)); return r; }
DEVI uint32_t hfma2(uint32_t a, uint32_t b, uint32_t c) { uint32_t r; asm("fma.rn.bf16x2 %0, %1, %2, %3;" : "=r"(r) : "r"(a), "r"(b), "r"(c)); return r; }
DEVI void landed(uint32_t v) { asm volatile("{\n.reg .pred p;\nsetp.eq.u32 p, %0, 0x7fc17fc1;\n@p st.shared.u32 [%1], %0;\n}" ::"r"(v), "r"(EPO + 8) : "memory"); }
DEVI void nb_sync_p(int on, int id, int n) { asm volatile("{\n.reg .pred p;\nsetp.ne.u32 p, %2, 0;\n@p bar.sync %0, %1;\n}" ::"r"(id), "r"(n), "r"(on) : "memory"); }
DEVI void nb_arrive_p(int on, int id, int n) { asm volatile("{\n.reg .pred p;\nsetp.ne.u32 p, %2, 0;\n@p bar.arrive %0, %1;\n}" ::"r"(id), "r"(n), "r"(on) : "memory"); }
DEVI void stsm4_p(int on, uint32_t a, uint32_t r0, uint32_t r1, uint32_t r2, uint32_t r3) {
  asm volatile("{\n.reg .pred p;\nsetp.ne.u32 p, %5, 0;\n@p stmatrix.sync.aligned.m8n8.x4.shared.b16 [%0], {%1,%2,%3,%4};\n}" ::"r"(a), "r"(r0), "r"(r1), "r"(r2), "r"(r3), "r"(on) : "memory");
}
DEVI void sts_f2_p(int on, uint32_t a, float x, float y) { asm volatile("{\n.reg .pred p;\nsetp.ne.u32 p, %3, 0;\n@p st.shared.v2.f32 [%0], {%1,%2};\n}" ::"r"(a), "f"(x), "f"(y), "r"(on) : "memory"); }
DEVI float rsq(float x) { float y; asm("rsqrt.approx.ftz.f32 %0, %1;" : "=f"(y) : "f"(x)); return y; }
DEVI void acc8(float (&c)[8], const uint4& v) {
  c[0] += bf_lo(v.x); c[1] += bf_hi(v.x); c[2] += bf_lo(v.y); c[3] += bf_hi(v.y);
  c[4] += bf_lo(v.z); c[5] += bf_hi(v.z); c[6] += bf_lo(v.w); c[7] += bf_hi(v.w);
}
template<int TB,uint32_t HA,uint32_t HB> DEVI void wg_ss_80(float (&d)[40], uint32_t a, uint32_t b){
  asm volatile("{\n.reg .b64 da, db;\nmov.b64 da, {%40, %42};\nmov.b64 db, {%41, %43};\nwgmma.mma_async.sync.aligned.m64n80k16.f32.bf16.bf16 {%0,%1,%2,%3,%4,%5,%6,%7,%8,%9,%10,%11,%12,%13,%14,%15,%16,%17,%18,%19,%20,%21,%22,%23,%24,%25,%26,%27,%28,%29,%30,%31,%32,%33,%34,%35,%36,%37,%38,%39}, da, db, 1, 1, 1, 0, %44;\n}\n"
    : "+f"(d[0]),"+f"(d[1]),"+f"(d[2]),"+f"(d[3]),"+f"(d[4]),"+f"(d[5]),"+f"(d[6]),"+f"(d[7]),"+f"(d[8]),"+f"(d[9]),"+f"(d[10]),"+f"(d[11]),"+f"(d[12]),"+f"(d[13]),"+f"(d[14]),"+f"(d[15]),"+f"(d[16]),"+f"(d[17]),"+f"(d[18]),"+f"(d[19]),"+f"(d[20]),"+f"(d[21]),"+f"(d[22]),"+f"(d[23]),"+f"(d[24]),"+f"(d[25]),"+f"(d[26]),"+f"(d[27]),"+f"(d[28]),"+f"(d[29]),"+f"(d[30]),"+f"(d[31]),"+f"(d[32]),"+f"(d[33]),"+f"(d[34]),"+f"(d[35]),"+f"(d[36]),"+f"(d[37]),"+f"(d[38]),"+f"(d[39])
    : "r"(a), "r"(b), "n"(HA), "n"(HB), "n"(TB));
}
template<int TB,uint32_t HA,uint32_t HB> DEVI void wg_ss_160(float (&d)[80], uint32_t a, uint32_t b){
  asm volatile("{\n.reg .b64 da, db;\nmov.b64 da, {%80, %82};\nmov.b64 db, {%81, %83};\nwgmma.mma_async.sync.aligned.m64n160k16.f32.bf16.bf16 {%0,%1,%2,%3,%4,%5,%6,%7,%8,%9,%10,%11,%12,%13,%14,%15,%16,%17,%18,%19,%20,%21,%22,%23,%24,%25,%26,%27,%28,%29,%30,%31,%32,%33,%34,%35,%36,%37,%38,%39,%40,%41,%42,%43,%44,%45,%46,%47,%48,%49,%50,%51,%52,%53,%54,%55,%56,%57,%58,%59,%60,%61,%62,%63,%64,%65,%66,%67,%68,%69,%70,%71,%72,%73,%74,%75,%76,%77,%78,%79}, da, db, 1, 1, 1, 0, %84;\n}\n"
    : "+f"(d[0]),"+f"(d[1]),"+f"(d[2]),"+f"(d[3]),"+f"(d[4]),"+f"(d[5]),"+f"(d[6]),"+f"(d[7]),"+f"(d[8]),"+f"(d[9]),"+f"(d[10]),"+f"(d[11]),"+f"(d[12]),"+f"(d[13]),"+f"(d[14]),"+f"(d[15]),"+f"(d[16]),"+f"(d[17]),"+f"(d[18]),"+f"(d[19]),"+f"(d[20]),"+f"(d[21]),"+f"(d[22]),"+f"(d[23]),"+f"(d[24]),"+f"(d[25]),"+f"(d[26]),"+f"(d[27]),"+f"(d[28]),"+f"(d[29]),"+f"(d[30]),"+f"(d[31]),"+f"(d[32]),"+f"(d[33]),"+f"(d[34]),"+f"(d[35]),"+f"(d[36]),"+f"(d[37]),"+f"(d[38]),"+f"(d[39]),"+f"(d[40]),"+f"(d[41]),"+f"(d[42]),"+f"(d[43]),"+f"(d[44]),"+f"(d[45]),"+f"(d[46]),"+f"(d[47]),"+f"(d[48]),"+f"(d[49]),"+f"(d[50]),"+f"(d[51]),"+f"(d[52]),"+f"(d[53]),"+f"(d[54]),"+f"(d[55]),"+f"(d[56]),"+f"(d[57]),"+f"(d[58]),"+f"(d[59]),"+f"(d[60]),"+f"(d[61]),"+f"(d[62]),"+f"(d[63]),"+f"(d[64]),"+f"(d[65]),"+f"(d[66]),"+f"(d[67]),"+f"(d[68]),"+f"(d[69]),"+f"(d[70]),"+f"(d[71]),"+f"(d[72]),"+f"(d[73]),"+f"(d[74]),"+f"(d[75]),"+f"(d[76]),"+f"(d[77]),"+f"(d[78]),"+f"(d[79])
    : "r"(a), "r"(b), "n"(HA), "n"(HB), "n"(TB));
}
template<int TB,uint32_t HA,uint32_t HB> DEVI void wg_ss_192(float (&d)[96], uint32_t a, uint32_t b){
  asm volatile("{\n.reg .b64 da, db;\nmov.b64 da, {%96, %98};\nmov.b64 db, {%97, %99};\nwgmma.mma_async.sync.aligned.m64n192k16.f32.bf16.bf16 {%0,%1,%2,%3,%4,%5,%6,%7,%8,%9,%10,%11,%12,%13,%14,%15,%16,%17,%18,%19,%20,%21,%22,%23,%24,%25,%26,%27,%28,%29,%30,%31,%32,%33,%34,%35,%36,%37,%38,%39,%40,%41,%42,%43,%44,%45,%46,%47,%48,%49,%50,%51,%52,%53,%54,%55,%56,%57,%58,%59,%60,%61,%62,%63,%64,%65,%66,%67,%68,%69,%70,%71,%72,%73,%74,%75,%76,%77,%78,%79,%80,%81,%82,%83,%84,%85,%86,%87,%88,%89,%90,%91,%92,%93,%94,%95}, da, db, 1, 1, 1, 0, %100;\n}\n"
    : "+f"(d[0]),"+f"(d[1]),"+f"(d[2]),"+f"(d[3]),"+f"(d[4]),"+f"(d[5]),"+f"(d[6]),"+f"(d[7]),"+f"(d[8]),"+f"(d[9]),"+f"(d[10]),"+f"(d[11]),"+f"(d[12]),"+f"(d[13]),"+f"(d[14]),"+f"(d[15]),"+f"(d[16]),"+f"(d[17]),"+f"(d[18]),"+f"(d[19]),"+f"(d[20]),"+f"(d[21]),"+f"(d[22]),"+f"(d[23]),"+f"(d[24]),"+f"(d[25]),"+f"(d[26]),"+f"(d[27]),"+f"(d[28]),"+f"(d[29]),"+f"(d[30]),"+f"(d[31]),"+f"(d[32]),"+f"(d[33]),"+f"(d[34]),"+f"(d[35]),"+f"(d[36]),"+f"(d[37]),"+f"(d[38]),"+f"(d[39]),"+f"(d[40]),"+f"(d[41]),"+f"(d[42]),"+f"(d[43]),"+f"(d[44]),"+f"(d[45]),"+f"(d[46]),"+f"(d[47]),"+f"(d[48]),"+f"(d[49]),"+f"(d[50]),"+f"(d[51]),"+f"(d[52]),"+f"(d[53]),"+f"(d[54]),"+f"(d[55]),"+f"(d[56]),"+f"(d[57]),"+f"(d[58]),"+f"(d[59]),"+f"(d[60]),"+f"(d[61]),"+f"(d[62]),"+f"(d[63]),"+f"(d[64]),"+f"(d[65]),"+f"(d[66]),"+f"(d[67]),"+f"(d[68]),"+f"(d[69]),"+f"(d[70]),"+f"(d[71]),"+f"(d[72]),"+f"(d[73]),"+f"(d[74]),"+f"(d[75]),"+f"(d[76]),"+f"(d[77]),"+f"(d[78]),"+f"(d[79]),"+f"(d[80]),"+f"(d[81]),"+f"(d[82]),"+f"(d[83]),"+f"(d[84]),"+f"(d[85]),"+f"(d[86]),"+f"(d[87]),"+f"(d[88]),"+f"(d[89]),"+f"(d[90]),"+f"(d[91]),"+f"(d[92]),"+f"(d[93]),"+f"(d[94]),"+f"(d[95])
    : "r"(a), "r"(b), "n"(HA), "n"(HB), "n"(TB));
}
template<int SD,int TB,uint32_t HB> DEVI void wg_rs_64(float (&d)[32], uint32_t a0, uint32_t a1, uint32_t a2, uint32_t a3, uint32_t b){
  asm volatile("{\n.reg .b64 db;\nmov.b64 db, {%36, %37};\nwgmma.mma_async.sync.aligned.m64n64k16.f32.bf16.bf16 {%0,%1,%2,%3,%4,%5,%6,%7,%8,%9,%10,%11,%12,%13,%14,%15,%16,%17,%18,%19,%20,%21,%22,%23,%24,%25,%26,%27,%28,%29,%30,%31}, {%32,%33,%34,%35}, db, %38, 1, 1, %39;\n}\n"
    : "+f"(d[0]),"+f"(d[1]),"+f"(d[2]),"+f"(d[3]),"+f"(d[4]),"+f"(d[5]),"+f"(d[6]),"+f"(d[7]),"+f"(d[8]),"+f"(d[9]),"+f"(d[10]),"+f"(d[11]),"+f"(d[12]),"+f"(d[13]),"+f"(d[14]),"+f"(d[15]),"+f"(d[16]),"+f"(d[17]),"+f"(d[18]),"+f"(d[19]),"+f"(d[20]),"+f"(d[21]),"+f"(d[22]),"+f"(d[23]),"+f"(d[24]),"+f"(d[25]),"+f"(d[26]),"+f"(d[27]),"+f"(d[28]),"+f"(d[29]),"+f"(d[30]),"+f"(d[31])
    : "r"(a0),"r"(a1),"r"(a2),"r"(a3), "r"(b), "n"(HB), "n"(SD), "n"(TB));
}
template<int SD,int TB,uint32_t HB> DEVI void wg_rs_128(float (&d)[64], uint32_t a0, uint32_t a1, uint32_t a2, uint32_t a3, uint32_t b){
  asm volatile("{\n.reg .b64 db;\nmov.b64 db, {%68, %69};\nwgmma.mma_async.sync.aligned.m64n128k16.f32.bf16.bf16 {%0,%1,%2,%3,%4,%5,%6,%7,%8,%9,%10,%11,%12,%13,%14,%15,%16,%17,%18,%19,%20,%21,%22,%23,%24,%25,%26,%27,%28,%29,%30,%31,%32,%33,%34,%35,%36,%37,%38,%39,%40,%41,%42,%43,%44,%45,%46,%47,%48,%49,%50,%51,%52,%53,%54,%55,%56,%57,%58,%59,%60,%61,%62,%63}, {%64,%65,%66,%67}, db, %70, 1, 1, %71;\n}\n"
    : "+f"(d[0]),"+f"(d[1]),"+f"(d[2]),"+f"(d[3]),"+f"(d[4]),"+f"(d[5]),"+f"(d[6]),"+f"(d[7]),"+f"(d[8]),"+f"(d[9]),"+f"(d[10]),"+f"(d[11]),"+f"(d[12]),"+f"(d[13]),"+f"(d[14]),"+f"(d[15]),"+f"(d[16]),"+f"(d[17]),"+f"(d[18]),"+f"(d[19]),"+f"(d[20]),"+f"(d[21]),"+f"(d[22]),"+f"(d[23]),"+f"(d[24]),"+f"(d[25]),"+f"(d[26]),"+f"(d[27]),"+f"(d[28]),"+f"(d[29]),"+f"(d[30]),"+f"(d[31]),"+f"(d[32]),"+f"(d[33]),"+f"(d[34]),"+f"(d[35]),"+f"(d[36]),"+f"(d[37]),"+f"(d[38]),"+f"(d[39]),"+f"(d[40]),"+f"(d[41]),"+f"(d[42]),"+f"(d[43]),"+f"(d[44]),"+f"(d[45]),"+f"(d[46]),"+f"(d[47]),"+f"(d[48]),"+f"(d[49]),"+f"(d[50]),"+f"(d[51]),"+f"(d[52]),"+f"(d[53]),"+f"(d[54]),"+f"(d[55]),"+f"(d[56]),"+f"(d[57]),"+f"(d[58]),"+f"(d[59]),"+f"(d[60]),"+f"(d[61]),"+f"(d[62]),"+f"(d[63])
    : "r"(a0),"r"(a1),"r"(a2),"r"(a3), "r"(b), "n"(HB), "n"(SD), "n"(TB));
}

#define STAMP(i)
#define STAMPW(i)

DEVI uint32_t sw64(uint32_t row, uint32_t c) { return row * 64 + ((c ^ ((row >> 1) & 3)) << 4); }
DEVI uint32_t sw128(uint32_t row, uint32_t c) { return row * 128 + ((c ^ (row & 7)) << 4); }

DEVI float gelu_s(float t, float k0, float k1, float hr) {
  const float h = t * hr;
  return fmaf(h, tanh_fast(t * fmaf(t * t, k1, k0)), h);
}
template <int NU, int SZ>
DEVI void gelu_store(int on, const float (&e)[SZ], float mu0, float mu1, float rs0, float rs1, uint32_t cb, uint32_t c4, uint32_t aE, uint32_t aO, uint32_t a4) {
  uint32_t pk[NU * 4];
  const float a0 = 0.7978845608f * rs0, a1 = 0.0356774081f * rs0 * rs0 * rs0, ah = 0.5f * rs0;
  const float b0 = 0.7978845608f * rs1, b1 = 0.0356774081f * rs1 * rs1 * rs1, bh = 0.5f * rs1;
#pragma unroll
  for (int j = 0; j < NU * 2; j++) {
    const float2 c = lds_f2((j >= 8 ? c4 - 256 : cb) + j * 32);
    const float* a = &e[j * 4];
    pk[2 * j] = pack2(gelu_s(fmaf(-mu0, c.x, a[0]), a0, a1, ah), gelu_s(fmaf(-mu0, c.y, a[1]), a0, a1, ah));
    pk[2 * j + 1] = pack2(gelu_s(fmaf(-mu1, c.x, a[2]), b0, b1, bh), gelu_s(fmaf(-mu1, c.y, a[3]), b0, b1, bh));
  }
  nb_sync_p(on, NB_FREE, 288);
#pragma unroll
  for (int j = 0; j < NU; j++) stsm4_p(on, j == 4 ? a4 : ((j & 1) ? aO : aE) + (j >> 1) * 4096, pk[4 * j], pk[4 * j + 1], pk[4 * j + 2], pk[4 * j + 3]);
  fence_async_smem();
  nb_arrive_p(on, NB_RDY, 288);
}

DEVI void mlp_role(const Params& P, int b, int q, int wg, uint32_t t_start) {
  const int tid = threadIdx.x, lane = tid & 31, w = (tid >> 5) & 3;
  const int odd = q & 1;
  const int r0 = 16 * w + (lane >> 2);
  const int srow = 16 * w + (lane & 7) + ((lane >> 3) & 1) * 8;
  const int schk = lane >> 4;
  uint32_t phM = 0;
  uint32_t s = 0, sp = 0;
  const bool rel = (tid & 127) == 0;
#define STAGE_WAIT() mbar_wait(B_FM + s * 8, (phM >> s) & 1); phM ^= 1u << s; const uint32_t so = s * SL16; wg_fence();
#define STAGE_NEXT() wg_commit(); wg_wait<1>(); if (rel && it > 0) mbar_arrive(B_EM + sp * 8); sp = s; s = s == NST - 1 ? 0 : s + 1;
#define STAGE_END() wg_wait<0>(); if (rel && on) mbar_arrive(B_EM + sp * 8);

  const int ga = 2 * wg + odd, gs = odd ? 0 : 4;
  const uint32_t oA = sw64(srow, schk), oB = sw64(srow, 2 + schk);
  constexpr uint32_t dA = dlo(SM, 16);
  const uint32_t dBlo = dlo(SM + 8192, 16384) + wg * (dlo(8192, 0) - dlo(0, 8192 - 32));
  const uint32_t dBhi = dBlo + dlo(4096, 0) - dlo(0, 4096 - 64);
  float mu0, mu1;
  const uint32_t o128 = srow * 128, x128 = ((srow & 7) ^ schk) << 4;
  uint32_t xf[20];
#pragma unroll
  for (int i = 0; i < 20; i++) xf[i] = 0;
  for (int on = 1; on < 2; on++) {
    float acc[40];
    zero(acc);
    const uint32_t dB1 = dBlo + dlo(4096, FB - SM - 28672);
#pragma unroll 1
    for (int it = 0; it < 10 * on; it++) {
      mbar_wait(B_FM + s * 8, (phM >> s) & 1); phM ^= 1u << s;
      const uint32_t so = s * SL16;
      if (wg == 0) STAMPW(82 + it);
      if (it == ((5 * q + 1) >> 1) + wg) {
#pragma unroll
        for (int j = 0; j < 4; j++) ldsm4(SM + s * SLOT + o128 + (x128 ^ (j << 5)), xf[4 * j], xf[4 * j + 1], xf[4 * j + 2], xf[4 * j + 3]);
        landed(xf[0] ^ xf[4] ^ xf[8] ^ xf[12]);
      }
      if (it == 2 + 5 * (q >> 1)) { ldsm4(SM + s * SLOT + o128 + (x128 ^ ((2 * odd + wg) << 5)), xf[16], xf[17], xf[18], xf[19]); landed(xf[16]); }
      const uint32_t dh = dB1 + so - s * dlo(0, SLOT - 4096);
      wg_fence();
#pragma unroll
      for (int kk = 0; kk < 4; kk++) wg_ss_80<1, H128, H128>(acc, dA + so + kk * 2, (kk < 2 ? dBlo + so : dh) + (kk & 1) * 128);
      STAGE_NEXT();
    }
    STAGE_END();
    if (rel && on) mbar_arrive(B_G1);
    STAMPW(wg * 16 + 12);
    const int carry = (b + (q & 2 ? 2 : 1) * (odd ? -1 : 1)) >> 5;
    const int drow = (srow + carry) & 63;
    const uint32_t dA_ = STG + sw64(drow, schk), dB_ = STG + sw64(drow, 2 + schk);
    nb_sync_p(on, NB_STATS, 416);
    const float4 s0 = lds_f4(ROW + r0 * 16), s1 = lds_f4(ROW + 128 + r0 * 16);
    mu0 = s0.x; mu1 = s1.x;
    const float rs0 = (r0 + carry < 0) ? 0.f : s0.z, rs1 = (r0 + 8 + carry >= 64) ? 0.f : s1.z;
    pin(acc);
    STAMPW(wg * 16 + 1);
    gelu_store<5>(on, acc, mu0, mu1, rs0, rs1, CS1 + ga * 128 + (lane & 3) * 8, CS1 + gs * 128 + wg * 64 + (lane & 3) * 8,
                  ga * 4096 + dA_, ga * 4096 + dB_, gs * 4096 + (wg ? dB_ : dA_));
    STAMPW(wg * 16 + 2);
  }
  s = 16 % NST;
  for (int on = 1; on < 2; on++) {
    float acc[40];
    zero(acc);
    const float ra = __uint_as_float(lds_u32(ROW + 4 + r0 * 16)), rb = __uint_as_float(lds_u32(ROW + 132 + r0 * 16));
#pragma unroll 1
    for (int it = 0; it < 10 * on; it++) {
      STAGE_WAIT();
      if (it == 0) STAMPW(wg * 16 + 3);
#pragma unroll
      for (int kk = 0; kk < 4; kk++) wg_ss_80<1, H64, H128>(acc, dA + so + (kk >> 1) * 256 + (kk & 1) * 2, (kk < 2 ? dBlo : dBhi) + so + (kk & 1) * 128);
      STAGE_NEXT();
    }
    STAGE_END();
    pin(acc);
    STAMPW(wg * 16 + 4);
    const float n0 = -mu0 * ra, n1 = -mu1 * rb;
    float s0 = 0.f, s1 = 0.f;
    uint32_t yf[20];
#pragma unroll
    for (int j = 0; j < 10; j++) {
      float* a = &acc[j * 4];
      const uint32_t p0 = pack2(fmaf(bf_lo(xf[2 * j]), ra, n0) + a[0], fmaf(bf_hi(xf[2 * j]), ra, n0) + a[1]);
      const uint32_t p1 = pack2(fmaf(bf_lo(xf[2 * j + 1]), rb, n1) + a[2], fmaf(bf_hi(xf[2 * j + 1]), rb, n1) + a[3]);
      yf[2 * j] = p0; yf[2 * j + 1] = p1;
      a[0] = bf_lo(p0); a[1] = bf_hi(p0); a[2] = bf_lo(p1); a[3] = bf_hi(p1);
      s0 += a[0] + a[1]; s1 += a[2] + a[3];
    }
    nb_sync_p(on, NB_FREE, 288);
#pragma unroll
    for (int j = 0; j < 5; j++)
      stsm4_p(on, STG + (j == 4 ? gs * 4096 + (wg ? oB : oA) : (ga + (j >> 1)) * 4096 + ((j & 1) ? oB : oA)), yf[4 * j], yf[4 * j + 1], yf[4 * j + 2], yf[4 * j + 3]);
    s0 += __shfl_xor_sync(~0u, s0, 1); s1 += __shfl_xor_sync(~0u, s1, 1);
    s0 += __shfl_xor_sync(~0u, s0, 2); s1 += __shfl_xor_sync(~0u, s1, 2);
    const float m0 = s0 * (1.f / 80.f), m1 = s1 * (1.f / 80.f);
    float v0 = 0.f, v1 = 0.f;
#pragma unroll
    for (int j = 0; j < 10; j++) {
      const float* a = &acc[j * 4];
      const float d0 = a[0] - m0, d1 = a[1] - m0, d2 = a[2] - m1, d3 = a[3] - m1;
      v0 = fmaf(d0, d0, v0); v0 = fmaf(d1, d1, v0); v1 = fmaf(d2, d2, v1); v1 = fmaf(d3, d3, v1);
    }
    v0 += __shfl_xor_sync(~0u, v0, 1); v1 += __shfl_xor_sync(~0u, v1, 1);
    v0 += __shfl_xor_sync(~0u, v0, 2); v1 += __shfl_xor_sync(~0u, v1, 2);
    sts_f2_p((lane & 3) == 0, ST1 + wg * 512 + r0 * 8, m0, v0); sts_f2_p((lane & 3) == 0, ST1 + 64 + wg * 512 + r0 * 8, m1, v1);
    fence_async_smem();
    nb_arrive_p(on, NB_RDY, 288);
    STAMPW(wg * 16 + 5);
  }
  for (int on = 1; on < 2; on++) {
    float ac3[96];
    zero(ac3);
    const uint32_t dA3 = dA + wg * 256;
    constexpr uint32_t dB = dlo(SM + 8192, 4096);
    if (on) mbar_wait(B_FM + s * 8, (phM >> s) & 1);
    STAMPW(wg * 16 + 6);
    const float2* sp1 = P.sc->st1 + (((b & ~1) + wg) * 8 + 2 * (lane & 3)) * 64 + r0;
    float2 pa0 = {0.f, 0.f}, pa1 = pa0, pb0 = pa0, pb1 = pa0;
    if (on) { pa0 = ldg_cg_f2(sp1); pa1 = ldg_cg_f2(sp1 + 64); pb0 = ldg_cg_f2(sp1 + 8); pb1 = ldg_cg_f2(sp1 + 72); }
    float m0, m1, rs0, rs1;
#pragma unroll 1
    for (int it = 0; it < 20 * on; it++) {
      STAGE_WAIT();
      wg_ss_192<1, H64, H128>(ac3, dA3 + so, dB + so);
      wg_ss_192<1, H64, H128>(ac3, dA3 + so + 2, dB + so + 128);
      STAGE_NEXT();
    }
    m0 = pa0.x + pa1.x; m1 = pb0.x + pb1.x;
    m0 += __shfl_xor_sync(~0u, m0, 1); m1 += __shfl_xor_sync(~0u, m1, 1);
    m0 += __shfl_xor_sync(~0u, m0, 2); m1 += __shfl_xor_sync(~0u, m1, 2);
    m0 *= 0.125f; m1 *= 0.125f;
    const float d0 = pa0.x - m0, d1 = pa1.x - m0, d2 = pb0.x - m1, d3 = pb1.x - m1;
    float v0 = pa0.y + pa1.y + 80.f * (d0 * d0 + d1 * d1), v1 = pb0.y + pb1.y + 80.f * (d2 * d2 + d3 * d3);
    v0 += __shfl_xor_sync(~0u, v0, 1); v1 += __shfl_xor_sync(~0u, v1, 1);
    v0 += __shfl_xor_sync(~0u, v0, 2); v1 += __shfl_xor_sync(~0u, v1, 2);
    rs0 = rsq(v0 * (1.f / 640.f) + 1e-5f); rs1 = rsq(v1 * (1.f / 640.f) + 1e-5f);
    STAGE_END();
    STAMPW(wg * 16 + 7);
    nb_sync_p(on, NB_CS3, 288);
    pin(ac3);
#pragma unroll 1
    for (int r = 0; r < 1 + 2 * on; r++) {
      gelu_store<4>(on, ac3, m0, m1, rs0, rs1, CS3 + r * 256 + (lane & 3) * 8, 0, STG + wg * 8192 + oA, STG + wg * 8192 + oB, 0);
#pragma unroll
      for (int i = 0; i < 64; i++) ac3[i] = ac3[i + 32];
    }
    STAMPW(wg * 16 + 8);
  }
  for (int on = 1; on < 2; on++) {
  float acc[40];
  zero(acc);
#pragma unroll 1
  for (int it = 0; it < 24 * on; it++) {
    if ((uint32_t)(it - G5AT) < 10) s = s == NST - 1 ? 0 : s + 1;
    STAGE_WAIT();
    if (it == 0) STAMPW(wg * 16 + 9);
#pragma unroll
    for (int kk = 0; kk < 4; kk++) wg_ss_80<1, H64, H128>(acc, dA + so + (kk >> 1) * 256 + (kk & 1) * 2, (kk < 2 ? dBlo : dBhi) + so + (kk & 1) * 128);
    STAGE_NEXT();
  }
  nb_sync_p(on, NB_S, 384);
  nb_sync_p(on, NB_FREE, 288);
  constexpr uint32_t SX = SM + (80 % NST) * SLOT, SY = SM + (81 % NST) * SLOT;
  if (on) { mbar_wait(B_FM + (80 % NST) * 8, (phM >> (80 % NST)) & 1); mbar_wait(B_FM + (81 % NST) * 8, (phM >> (81 % NST)) & 1); }
  wg_wait<0>();
  pin(acc);
  STAMPW(wg * 16 + 10);
  const uint32_t o32 = 16384 + wg * 2048 + srow * 32 + ((schk ^ ((srow >> 2) & 1)) << 4);
#pragma unroll
  for (int j = 0; j < 5; j++) {
    uint32_t sv[4], xv[4], yv[4], o[4];
    const uint32_t ot = j < 4 ? wg * 8192 + o128 + (x128 ^ (j << 5)) : o32;
    ldsm4(FB + (j < 4 ? ot : 16384 + o128 + (x128 ^ (wg << 5))), sv[0], sv[1], sv[2], sv[3]);
    ldsm4(SX + ot, xv[0], xv[1], xv[2], xv[3]);
    ldsm4(SY + wg * 12288 + (j >> 1) * 4096 + ((j < 4 ? j & 1 : odd) ? oB : oA), yv[0], yv[1], yv[2], yv[3]);
#pragma unroll
    for (int u = 0; u < 4; u++) {
      const int f = 4 * j + u;
      const float g0 = silu(bf_lo(yv[u]) + acc[2 * f]), g1 = silu(bf_hi(yv[u]) + acc[2 * f + 1]);
      o[u] = pack2(fmaf(bf_lo(sv[u]), g0, bf_lo(xv[u])), fmaf(bf_hi(sv[u]), g1, bf_hi(xv[u])));
    }
    stsm4_p(on, STG + ot, o[0], o[1], o[2], o[3]);
  }
  fence_async_smem();
  nb_arrive_p(on, NB_RDY, 288);
  STAMPW(wg * 16 + 11);
  }
#undef STAGE_WAIT
#undef STAGE_NEXT
#undef STAGE_END
}

DEVI void e_frags(uint32_t (&Cf)[16], uint32_t (&Sf)[16], int r0, int lane, uint32_t sneg) {
#pragma unroll
  for (int i = 0; i < 4; i++) {
    const int row = r0 + 8 * (i & 1), i0 = row * (8 * (i >> 1) + 2 * (lane & 3)) + 32;
    const float a0 = (float)((i0 & 63) - 32) * 0.09817477042468103f, a1 = (float)(((i0 + row) & 63) - 32) * 0.09817477042468103f;
    Cf[i] = pack2(__cosf(a0), __cosf(a1)); Sf[i] = pack2(__sinf(a0), __sinf(a1));
  }
  const bool sw = r0 & 1;
  const uint32_t N = 0x80008000u, m1 = sw ? N : 0u;
  const uint32_t nc = ((r0 + 1) & 2) ? N : 0u, ns = ((r0 & 2) ? N : 0u) ^ sneg;
#pragma unroll
  for (int i = 0; i < 4; i++) {
    Cf[4 + i] = (sw ? Sf[i] : Cf[i]) ^ nc; Sf[4 + i] = (sw ? Cf[i] : Sf[i]) ^ ns;
    Sf[i] ^= sneg;
    Cf[8 + i] = Cf[i] ^ m1; Sf[8 + i] = Sf[i] ^ m1; Cf[12 + i] = Cf[4 + i] ^ m1; Sf[12 + i] = Sf[4 + i] ^ m1;
  }
}
DEVI void d_frags(uint32_t (&D)[8], int c0, int cs, int lane) {
#pragma unroll
  for (int i = 0; i < 4; i++) {
    const int v = c0 + cs * (8 * i + 2 * (lane & 3)) + 1024;
    const float a0 = (float)((v & 2047) - 1024) * 0.0030679615757712823f, a1 = (float)(((v + cs) & 2047) - 1024) * 0.0030679615757712823f;
    D[2 * i] = pack2(__cosf(a0), __cosf(a1)); D[2 * i + 1] = pack2(__sinf(a0), __sinf(a1));
  }
}

DEVI void s_step(const uint32_t (&Cf)[16], const uint32_t (&Sf)[16], int na, uint32_t sbase, uint32_t sx) {
#pragma unroll 1
  for (int i = 0; i < na; i++) {
    const uint32_t dU = dlo(FB, 8192) + i * 512;
    float p[32], r[32];
    zero(p); zero(r);
    wg_fence();
    wg_rs_64<0, 1, H128>(p, Cf[0], Cf[1], Cf[2], Cf[3], dU);
    wg_rs_64<0, 1, H128>(r, Sf[0], Sf[1], Sf[2], Sf[3], dU);
#pragma unroll
    for (int kk = 1; kk < 4; kk++) {
      wg_rs_64<1, 1, H128>(p, Cf[4 * kk], Cf[4 * kk + 1], Cf[4 * kk + 2], Cf[4 * kk + 3], dU + kk * 128);
      wg_rs_64<1, 1, H128>(r, Sf[4 * kk], Sf[4 * kk + 1], Sf[4 * kk + 2], Sf[4 * kk + 3], dU + kk * 128);
    }
    wg_commit(); wg_wait<0>();
    pin(p); pin(r);
    nb_sync(NB_WG2, 128);
#pragma unroll
    for (int j = 0; j < 4; j++) {
      uint32_t o[4];
#pragma unroll
      for (int u = 0; u < 4; u++) { const int f = 2 * (4 * j + u); o[u] = pack2(p[f] + r[f + 1], p[f + 1] - r[f]); }
      stsm4(sbase + i * 8192 + (sx ^ (j << 5)), o[0], o[1], o[2], o[3]);
    }
  }
  fence_async_smem();
  nb_arrive(NB_DMA, 160);
}

DEVI void fft_role(const Params& P, int slot, int w, uint32_t t_start) {
  const int b = slot >> 2, q = slot & 3, odd = q & 1;
  const int t = threadIdx.x & 127, lane = t & 31;
  const int r0 = 16 * w + (lane >> 2);
  const int srow = 16 * w + (lane & 7) + ((lane >> 3) & 1) * 8;
  const uint32_t sbase = FB + srow * 128, sx = ((srow & 7) ^ (lane >> 4)) << 4;
  const int k1 = slot >> 1, hh = slot & 1;

  uint32_t ep;
  {
    const __nv_bfloat16* p = P.px + (32 * (16 * q + (t >> 3)) + b) * 640 + 8 * (t & 7);
    uint4 ev[10];
#pragma unroll
    for (int i = 0; i < 10; i++) ev[i] = ldg_nc_u4(p + i * 64);
    float c[4], d[4];
    zero(c); zero(d);
#pragma unroll
    for (int i = 0; i < 10; i++) {
      const uint32_t e[4] = {ev[i].x, ev[i].y, ev[i].z, ev[i].w};
#pragma unroll
      for (int k = 0; k < 4; k++) {
        const float lo = bf_lo(e[k]), hi = bf_hi(e[k]);
        c[k] += lo + hi; d[k] = fmaf(lo, lo, fmaf(hi, hi, d[k]));
      }
    }
    float a = (c[0] + c[1]) + (c[2] + c[3]), g = (d[0] + d[1]) + (d[2] + d[3]);
#pragma unroll
    for (int o = 1; o < 8; o <<= 1) { a += __shfl_xor_sync(~0u, a, o); g += __shfl_xor_sync(~0u, g, o); }
    const float m = a * (1.f / 640.f), var = fmaxf(fmaf(-m, m, g * (1.f / 640.f)), 0.f), r1 = rsq(var + 1e-5f);
    mbar_wait(B_EP, 0);
    ep = lds_u32(EPO);
    if ((t & 7) == 0)
      asm volatile("st.relaxed.gpu.global.v4.f32 [%0], {%1,%2,%3,%4};" ::"l"(P.sc->row + b * 64 + 16 * q + (t >> 3)), "f"(m), "f"(r1),
                   "f"(r1 * rsq(var * r1 * r1 + 1e-5f)), "f"(__uint_as_float(ep)) : "memory");
    __syncwarp();
    STAMPW(78);
  }
  {
    uint32_t Cf[16], Sf[16];
    {
      {
        const float* csp = P.sc->cs1 + 160 * q + 2 * min(t, 79);
        uint2 cp[4];
#pragma unroll 1
        for (int n = 0;; n++) {
#pragma unroll
          for (int k = 0; k < 4; k++) asm volatile("ld.relaxed.gpu.global.v2.u32 {%0,%1}, [%2];" : "=r"(cp[k].x), "=r"(cp[k].y) : "l"(csp + k * 640) : "memory");
          if (!__any_sync(~0u, ((cp[0].x ^ ep) | (cp[1].x ^ ep) | (cp[2].x ^ ep) | (cp[3].x ^ ep) | (cp[0].y ^ ep) | (cp[1].y ^ ep) | (cp[2].y ^ ep) | (cp[3].y ^ ep)) & 1)) break;
          if (n > SPIN_MAX) __trap();
        }
        if (t < 80) sts_f2(CS1 + t * 8, (__uint_as_float(cp[0].x) + __uint_as_float(cp[1].x)) + (__uint_as_float(cp[2].x) + __uint_as_float(cp[3].x)),
                           (__uint_as_float(cp[0].y) + __uint_as_float(cp[1].y)) + (__uint_as_float(cp[2].y) + __uint_as_float(cp[3].y)));
        __syncwarp();
        nb_arrive(NB_STATS, 416);
        STAMPW(29);
      }
      mbar_wait(B_ROW, 0);
      const float2 sa = lds_f2(ROW + r0 * 16), sb = lds_f2(ROW + 128 + r0 * 16);
      const float km = odd ? 0.f : -2.f;
      const uint32_t np0 = pack2(sa.x * km, sa.x * km), np1 = pack2(sb.x * km, sb.x * km), sg = odd ? 0xbf80bf80u : 0x3f803f80u;
      float acc[80];
      zero(acc);
      uint32_t s = 5, sp = 0, xb = SM + 4 * SLOT + srow * 128;
      mbar_wait(B_FF + 4 * 8, 0);
#pragma unroll 1
      for (int it = 0; it < 5; it++) {
        const uint32_t xa = SM + srow * 128 + s * SLOT;
        mbar_wait(B_FF + s * 8, 0);
        if (it == 2) { mbar_wait(B_FFT, 0); xb = sbase; }
        STAMPW(66 + it);
        uint32_t u[16], v[16];
#pragma unroll
        for (int kk = 0; kk < 4; kk++) {
          ldsm4(xa + (sx ^ (kk << 5)), u[4 * kk], u[4 * kk + 1], u[4 * kk + 2], u[4 * kk + 3]);
          ldsm4(xb + (sx ^ (kk << 5)), v[4 * kk], v[4 * kk + 1], v[4 * kk + 2], v[4 * kk + 3]);
        }
#pragma unroll
        for (int kk = 0; kk < 4; kk++)
          stsm4(xa + (sx ^ (kk << 5)), hfma2(v[4 * kk], sg, hadd2(u[4 * kk], np0)), hfma2(v[4 * kk + 1], sg, hadd2(u[4 * kk + 1], np1)),
                hfma2(v[4 * kk + 2], sg, hadd2(u[4 * kk + 2], np0)), hfma2(v[4 * kk + 3], sg, hadd2(u[4 * kk + 3], np1)));
        fence_async_smem();
        nb_sync(NB_WG2, 128);
        if (it == 1 && t == 0) mbar_arrive_n(B_EM + 4 * 8, 2);
        const uint32_t a = dlo(SM, 16) + s * SL16;
        wg_fence();
#pragma unroll
        for (int kk = 0; kk < 4; kk++) wg_ss_160<0, H128, H128>(acc, a + 2 * kk, a + 512 + 2 * kk);
        wg_commit();
        wg_wait<1>();
        if (it > 0 && t == 0) mbar_arrive_n(B_EM + sp * 8, 2);
        xb += 8192;
        sp = s; s = s == NST - 1 ? 0 : s + 1;
      }
      e_frags(Cf, Sf, r0, lane, 0);
      const float ra = sa.y, rb = sb.y;
      wg_wait<0>();
      if (t == 0) mbar_arrive_n(B_EM + 3 * 8, 2);
      pin(acc);
      STAMPW(34);
#pragma unroll
      for (int j = 0; j < 10; j++) {
        const float* a = &acc[j * 8];
        stsm4(sbase + (j >> 2) * 8192 + (sx ^ ((j & 3) << 5)), pack2(a[0] * ra, a[1] * ra), pack2(a[2] * rb, a[3] * rb),
              pack2(a[4] * ra, a[5] * ra), pack2(a[6] * rb, a[7] * rb));
      }
      fence_async_smem();
      nb_sync(NB_WG2, 128);
    }
    s_step(Cf, Sf, 3, sbase, sx);
    STAMPW(35);
  }
  {
    uint32_t nr = 0, ni = 0;
    const bool nyq = hh == 0 && (lane & 3) == 0;
    if (nyq) { const int o = (k1 + 64 * (8 * w + (lane >> 2))) * 321 + 320; nr = ldg_nc_u16(P.pwr + o); ni = ldg_nc_u16(P.pwi + o); }
    uint32_t D32[8], Di[8];
    {
      const int u = 8 * w + (lane >> 2);
      d_frags(D32, 0, k1 + 64 * u, lane);
      d_frags(Di, u * k1, 64 * u, lane);
    }
    uint32_t wf[48];
    mbar_wait(B_FFT, 1);
    {
      const uint32_t a = FB + (8 * w + (lane >> 2)) * 336 + (((k1 & 7) >> 1) + (lane & 3)) * 4;
      const uint32_t se = (k1 & 1) ? 0x7632 : 0x5410, so_ = se ^ 0x2222, ao = a + (k1 & 1) * 4;
#pragma unroll
      for (int j = 0; j < 20; j++) {
        wf[j] = __byte_perm(lds_u32(a + j * 16), lds_u32(a + 10752 + j * 16), se);
        wf[20 + j] = __byte_perm(lds_u32(ao + j * 16), lds_u32(ao + 10752 + j * 16), so_);
      }
#pragma unroll
      for (int j = 40; j < 48; j++) wf[j] = 0;
    }
    if (nyq) wf[0] = pack2(0.5f * bf_lo(nr), 0.5f * bf_lo(ni));
    landed(wf[39] ^ wf[19]);
    nb_arrive(NB_DMA, 160);
    STAMPW(36);
    mbar_wait(B_FFT, 0);
    STAMPW(38);
    const uint32_t vbase = FB + (8 * w + (lane & 7)) * 128, vx = ((lane & 7) ^ (lane >> 3)) << 4;
#pragma unroll 1
    for (int pc = 0; pc < 6; pc++) {
      const int c = pc >= 3 ? pc - 3 : pc;
      const uint32_t dV = dlo(FB, 4096) + c * 512;
      float acc[64];
      zero(acc);
      wg_fence();
      wg_rs_128<0, 1, H128>(acc, D32[0], D32[1], D32[2], D32[3], dV);
      wg_rs_128<1, 1, H128>(acc, D32[4], D32[5], D32[6], D32[7], dV + 128);
      wg_commit(); wg_wait<0>();
      pin(acc);
      uint32_t o[16];
      if (pc < 3) {
#pragma unroll
        for (int i = 0; i < 16; i++) {
          const float* a = &acc[4 * i];
          const float xr = a[0] + a[3], xi = a[1] - a[2], wr = bf_lo(wf[i]), wi = bf_hi(wf[i]);
          o[i] = pack2(xr * wr - xi * wi, xr * wi + xi * wr);
        }
      } else {
#pragma unroll
        for (int i = 0; i < 16; i++) o[i] = pack2(acc[4 * i] - acc[4 * i + 3], acc[4 * i + 1] + acc[4 * i + 2]);
      }
#pragma unroll
      for (int i = 0; i < 32; i++) wf[i] = wf[i + 16];
#pragma unroll
      for (int i = 0; i < 16; i++) wf[32 + i] = o[i];
      if (c == 2) {
        nb_sync(NB_WG2, 128);
#pragma unroll
        for (int j = 0; j < 10; j++) stsm4(vbase + (j >> 1) * 4096 + (vx ^ ((j & 1) << 6)), wf[4 * j], wf[4 * j + 1], wf[4 * j + 2], wf[4 * j + 3]);
        fence_async_smem();
#pragma unroll
        for (int j = 0; j < 8; j++) D32[j] = Di[j];
        if (pc == 2) nb_sync(NB_WG2, 128);
      }
    }
    nb_arrive(NB_DMA, 160);
    STAMPW(39);
  }
  {
    uint32_t Cf[16], Sf[16];
    e_frags(Cf, Sf, r0, lane, 0x80008000u);
    mbar_wait(B_FFT, 1);
    STAMPW(42);
    s_step(Cf, Sf, 3 - odd, sbase, sx);
    STAMPW(43);
  }
  {
    float p[40], r[40];
    zero(p); zero(r);
    uint32_t s = (46 + G5AT) % NST, phF = 0x3f;
#pragma unroll 1
    for (int hf = 0; hf < 2; hf++) {
#pragma unroll
      for (int i5 = 0; i5 < 5; i5++) {
        const uint32_t a = dlo(SM, 16) + s * SL16;
        mbar_wait(B_FF + s * 8, (phF >> s) & 1); phF ^= 1u << s;
        wg_fence();
#pragma unroll
        for (int kk = 0; kk < 4; kk++) {
          if (4 * i5 + kk < 10) wg_ss_80<0, H128, H128>(p, a + 2 * kk, a + 512 + 2 * kk);
          else wg_ss_80<0, H128, H128>(r, a + 2 * kk, a + 512 + 2 * kk);
        }
        wg_commit();
        wg_wait<0>();
        if (t == 0) mbar_arrive_n(B_EM + s * 8, 2);
        s = s >= NST - 2 ? s + 2 - NST : s + 2;
      }
    }
    pin(p); pin(r);
    STAMPW(45);
    const float sc = 2.f / (2048.f * 640.f);
#pragma unroll
    for (int j = 0; j < 5; j++) {
      uint32_t o0[4], o1[4];
#pragma unroll
      for (int u = 0; u < 4; u++) {
        const int f = 8 * j + 2 * u;
        const float a0 = p[f] * sc, a1 = p[f + 1] * sc;
        o0[u] = pack2(fmaf(r[f], sc, a0), fmaf(r[f + 1], sc, a1)); o1[u] = pack2(fmaf(r[f], -sc, a0), fmaf(r[f + 1], -sc, a1));
      }
      stsm4(sbase + (j < 4 ? (sx ^ (j << 5)) : 16384 + sx), o0[0], o0[1], o0[2], o0[3]);
      stsm4(sbase + (j < 4 ? 8192 + (sx ^ (j << 5)) : 16384 + (sx ^ 32)), o1[0], o1[1], o1[2], o1[3]);
    }
  }
  nb_arrive(NB_S, 384);
}

DEVI void helper_role(const Params& P, int slot, int warp, uint32_t t_start) {
  const int tid = threadIdx.x, q = slot & 3;
  const int n2 = q == 3 ? 1 : 3;
  if (warp == 14 && elect()) { bulk_st(P.sc->tab + 786432 + q * 8192, HTB, 8192); bulk_commit(); bulk_wait_all(); flag_add(P.sc, F_TAB); }
  if (tid == 480) { const uint32_t ep = P.sc->epoch[slot] + 1; P.sc->epoch[slot] = ep; sts_u32(EPO, ep); }
  {
    float c[8];
    zero(c);
    const int rg = tid / 80;
    if (tid < 400) {
#pragma unroll 1
      for (int ch = 0; ch < 8; ch++) {
        mbar_wait(BAR + (4 + ch) * 8, 0);
#pragma unroll
        for (int i = 0; i < 4; i++) acc8(c, lds_u4(SM + ch * 25600 + rg * 3840 + tid * 16 + i * 1280));
      }
    }
    __syncthreads();
    if (tid < 400) { sts_f4(SM + tid * 32, c[0], c[1], c[2], c[3]); sts_f4(SM + tid * 32 + 16, c[4], c[5], c[6], c[7]); }
    __syncthreads();
    if (tid < 320) {
      float x = 0.f, y = 0.f;
#pragma unroll
      for (int i = 0; i < 5; i++) { const float2 u = lds_f2(SM + i * 2560 + tid * 8); x += u.x; y += u.y; }
      const uint32_t tg = lds_u32(EPO) & 1;
      asm volatile("st.relaxed.gpu.global.v2.u32 [%0], {%1,%2};" ::"l"(P.sc->cs1 + q * 640 + tid * 2),
                   "r"((__float_as_uint(x) & ~1u) | tg), "r"((__float_as_uint(y) & ~1u) | tg) : "memory");
    }
    fence_async_smem();
    __syncthreads();
    if (warp == 0) STAMP(20);
  }
  if (warp == 15 && elect()) {
#pragma unroll 1
    for (int u = 0; u < 9; u++) {
      const int l = u / 3, t = 6 * q + u - 3;
      if (u == 3 * l) { mbar_arrive(BAR + l * 8); mbar_expect(BAR + l * 8, (l ? 3 : n2) * 16384); }
      if (l || u < n2) {
        const int row = l ? 192 * (t & 7) + 64 * (t >> 3) : 64 * (3 * q + u), col = l ? 256 : 128;
        tma_ld2(SM + u * 16384, l ? &P.w4h : &P.w2h, BAR + l * 8, col, row);
        tma_ld2(SM + u * 16384 + 8192, l ? &P.w4h : &P.w2h, BAR + l * 8, col + 320, row);
      }
    }
  }
#pragma unroll 1
  for (int l = 0; l < 3; l++) {
    const uint32_t buf = SM + l * 49152;
    const int k = tid >> 3, cc = tid & 7;
    mbar_wait(BAR + l * 8, 0);
    uint4 v[6];
#pragma unroll
    for (int u = 0; u < 6; u++) v[u] = lds_u4(buf + u * 8192 + sw128(k, cc));
    if (__syncthreads_or(v[5].x == 0x12345u) == 77) return;
#pragma unroll
    for (int u = 0; u < 6; u++) {
      const int qd = l ? cc >> 1 : 2 * (u & 1) + (cc >> 2), cd = l ? 2 * (u & 1) + (cc & 1) : cc & 3;
      sts_u4(buf + (u >> 1) * 16384 + qd * 4096 + sw128(k & 31, (k >> 5) * 4 + cd), v[u].x, v[u].y, v[u].z, v[u].w);
    }
    fence_async_smem();
    __syncthreads();
    if (warp == 12 && elect()) {
      bulk_st(P.sc->rem + (l ? 7 + 6 * q + 3 * l : 3 * q) * 16384, buf, (l ? 3 : n2) * 16384);
      bulk_commit(); bulk_wait_all(); flag_add(P.sc, l ? F_W4 : F_W2);
    }
    if (warp == 0) STAMP(l);
  }
  __syncthreads();
  const unsigned char* s3 = (const unsigned char*)P.pw3 + q * 491520;
  const uint32_t mo = SM + ((tid >= 192 ? 7 * 192 : 0) + tid) * 16;
  float c[8];
  zero(c);
#pragma unroll 1
  for (int ch = -4; ch < 10; ch++) {
    if (ch >= 0) {
      mbar_wait(BAR + (4 + (ch & 3)) * 8, ((ch >> 2) & 1) ^ 1);
      if (tid < 384) {
#pragma unroll
        for (int i = 0; i < 8; i++) acc8(c, lds_u4(mo + (ch & 3) * 49152 + i * 3072));
      }
      if (__syncthreads_or(c[0] == 12345.678f) == 77) return;
    }
    if (warp == 15 && ch < 6 && elect()) {
      const uint32_t mb = BAR + (4 + (ch & 3)) * 8;
      mbar_arrive(mb); mbar_expect(mb, 49152); bulk_ld(SM + (ch & 3) * 49152, s3 + (ch + 4) * 49152, 49152, mb);
    }
  }
  if (tid >= 192 && tid < 384) { sts_f4(SM + (tid - 192) * 32, c[0], c[1], c[2], c[3]); sts_f4(SM + (tid - 192) * 32 + 16, c[4], c[5], c[6], c[7]); }
  __syncthreads();
  if (tid < 192) {
    const float4 a = lds_f4(SM + tid * 32), d = lds_f4(SM + tid * 32 + 16);
    sts_f4(SM + tid * 32, c[0] + a.x, c[1] + a.y, c[2] + a.z, c[3] + a.w); sts_f4(SM + tid * 32 + 16, c[4] + d.x, c[5] + d.y, c[6] + d.z, c[7] + d.w);
  }
  fence_async_smem();
  __syncthreads();
  if (warp == 0) {
    if (elect()) { bulk_st(P.sc->cs3 + q * 1536, SM, 6144); bulk_commit(); bulk_wait_all(); flag_add(P.sc, F_CS3); }
    __syncwarp();
    STAMP(21);
    const uint32_t ep = lds_u32(EPO);
    flag_wait(P.sc, F_TAB, ep * 132);
  }
}

DEVI void l2_trickle(const Params& P, int slot, int lane, int a0, int a1) {
#pragma unroll 1
  for (int a = a0; a < a1; a++) {
    mbar_wait(a ? B_G1 : B_FM + 5 * 8, 0);
    const int n = a == 0 ? 6400 : a < 3 ? 10272 : 15360;
    const char* p = (const char*)(a == 0 ? P.pw2 : a == 1 ? P.pwr : a == 2 ? P.pwi : a == 3 ? P.pw3 : P.pw4) + slot * n;
#pragma unroll 1
    for (int o = 0; o < n; o += 4096) {
      if (o + lane * 128 < n) asm volatile("prefetch.global.L2 [%0];" ::"l"(p + o + lane * 128));
      __nanosleep(100);
    }
  }
}

DEVI void init_barriers() {
#pragma unroll
  for (int i = 0; i < NBAR; i++) mbar_init(BAR + i * 8, BAR + i * 8 <= B_G1 ? 2 : 1);
  asm volatile("fence.mbarrier_init.release.cluster;" ::: "memory");
}

__global__ void __launch_bounds__(512, 1) fused_kernel(const __grid_constant__ Params P) {
  extern __shared__ __align__(1024) unsigned char smem_raw[];
  const int tid = threadIdx.x, lane = tid & 31;
  const int warp = __shfl_sync(~0u, tid >> 5, 0);
  const uint32_t t_start = 0;
  int slot;
  uint32_t nsm; asm volatile("mov.u32 %0, %%nsmid;" : "=r"(nsm));
  if (nsm == 132) {
    uint32_t smid; asm volatile("mov.u32 %0, %%smid;" : "=r"(smid));
    if (smid < 64) slot = ((smid >> 1) & 7) * 16 + (smid >> 4) * 2 + (smid & 1);
    else if (smid < 120) { const uint32_t u = smid - 64, r = u / 14; slot = ((u >> 1) - 7 * r) * 16 + 24 + r * 2 + (u & 1); }
    else slot = smid < 124 ? smid + 8 : smid - 116;
  } else slot = blockIdx.x;
  const int b = slot >> 2, q = slot & 3, odd = q & 1;

  const int blkA = (5 * q + 1) >> 1, colS = 160 * q + (odd ? 0 : 128);
  if (warp == 12 && slot >= 128 && elect()) {
    init_barriers();
#pragma unroll 1
    for (int c = 0; c < 8; c++) {
      mbar_arrive(BAR + (4 + c) * 8); mbar_expect(BAR + (4 + c) * 8, 25600);
      bulk_ld(SM + c * 25600, (const unsigned char*)P.pw1 + q * 204800 + c * 25600, 25600, BAR + (4 + c) * 8);
    }
  }
  if (warp == 12 && slot < 128) {
    if (elect()) {
      init_barriers();
#pragma unroll 1
      for (int it = 0; it < NPRE; it++) {
        const uint32_t dst = SM + it * SLOT, fb = B_FM + it * 8;
        mbar_arrive(fb); mbar_expect(fb, 28672);
        const int k0 = it * 64;
        tma_ld3(dst, &P.x, fb, k0, b, 0);
        tma_ld3(dst + 8192, &P.w1a, fb, 0, k0, blkA); tma_ld2(dst + 24576, &P.w1b, fb, colS, k0); tma_ld2(FB + it * 4096, &P.w1b, fb, colS, k0 + 32);
      }
    }
    __syncwarp();
    nb_arrive(NB_INIT, 96); nb_arrive(NB_GO, 448);
    STAMP(72);
  }
  if (warp >= 12 && slot < 128) {
    asm volatile("setmaxnreg.dec.sync.aligned.u32 24;");
    uint32_t s = NPRE, ph = 1;
#define PSTEP(FULL_, bytes, ISSUE) { mbar_wait(B_EM + s * 8, ph); const uint32_t dst = SM + s * SLOT, fb = FULL_ + s * 8; \
      if (elect()) { mbar_expect(fb, bytes); ISSUE; } __syncwarp(); if (++s == NST) { s = 0; ph ^= 1; } }
    if (warp == 12) {
#pragma unroll 1
      for (int it = NPRE; it < 10; it++) {
        const int k0 = it * 64;
        PSTEP(B_FM, 20480, tma_ld3(dst + 8192, &P.w1a, fb, 0, k0, blkA); tma_ld2(dst + 24576, &P.w1b, fb, colS, k0); tma_ld2(FB + s * 4096, &P.w1b, fb, colS, k0 + 32));
        if (it == 5) STAMP(73);
      }
      s = 5;
      mbar_wait(B_EP, 0);
      const uint32_t ep = lds_u32(EPO);
      const unsigned char* src = P.sc->tab + q * 102400;
      flag_wait(P.sc, F_TAB, ep * 132);
      STAMP(47);
#pragma unroll 1
      for (int it = 0; it < 5; it++) PSTEP(B_FF, 20480, bulk_ld(dst + 8192, src + it * 20480, 20480, fb));
      const unsigned char* rem = P.sc->rem + q * 4096;
      flag_wait(P.sc, F_W2, ep * 4);
      STAMP(48);
#pragma unroll 1
      for (int it = 0; it < 10; it++) PSTEP(B_FM, 20480, tma_ld3(dst + 8192, &P.w2a, fb, 0, it * 64, blkA); bulk_ld(dst + 24576, rem + it * 16384, 4096, fb));
#pragma unroll 1
      for (int it = 0; it < 20; it++) PSTEP(B_FM, 12288, tma_ld3(dst + 8192, &P.w3, fb, 0, it * 32, 6 * q + 3 * (b & 1)));
      flag_wait(P.sc, F_W4, ep * 8);
#pragma unroll 1
      for (int it = 0; it < 24; it++) {
        if ((uint32_t)(it - G5AT) < 10) PSTEP(B_FF, 10240, bulk_ld(dst + 8192, src + 409600 + (it - G5AT) * 10240, 10240, fb));
        PSTEP(B_FM, 20480, tma_ld3(dst + 8192, &P.w4a, fb, 64 * q, 192 * (it & 7) + 64 * (it >> 3), 0); bulk_ld(dst + 24576, rem + (10 + it) * 16384, 4096, fb));
      }
    } else if (warp == 13) {
      if (elect()) { tmap_pf(&P.w1a); tmap_pf(&P.w1b); }
      nb_sync(NB_INIT, 96);
#pragma unroll 1
      for (int it = NPRE; it < 10; it++) PSTEP(B_FM, 8192, tma_ld3(dst, &P.x, fb, it * 64, b, 0));
      PSTEP(B_FF, 16384, mbar_arrive(fb); tma_ld3(dst, &P.x, fb, 320, b, 0); tma_ld3(dst + 8192, &P.x, fb, 384, b, 0));
#pragma unroll 1
      for (int it = 0; it < 5; it++) {
        if (it == 4) {
          mbar_wait(B_G1, 0);
          if (elect()) { mbar_expect(B_FFT, 24576); tma_ld3(FB, &P.x, B_FFT, 448, b, 0); tma_ld3(FB + 8192, &P.x, B_FFT, 512, b, 0); tma_ld3(FB + 16384, &P.x, B_FFT, 576, b, 0); }
          __syncwarp();
        }
        PSTEP(B_FF, 8192, tma_ld3(dst, &P.x, fb, it * 64, b, 0));
      }
      mbar_wait(B_EP, 0);
      const uint32_t ep = lds_u32(EPO);
      const unsigned char* src = P.sc->h + b * 81920;
      flag_wait(P.sc, F_H + (b >> 2), ep * 16);
      STAMP(52);
#pragma unroll 1
      for (int it = 0; it < 10; it++) PSTEP(B_FM, 8192, bulk_ld(dst, src + it * 8192, 8192, fb));
      src = P.sc->x1 + (b & ~1) * 81920;
      flag_wait(P.sc, F_X1 + (b >> 1), ep * 8);
      STAMP(53);
#pragma unroll 1
      for (int it = 0; it < 20; it++) PSTEP(B_FM, 8192, bulk_ld(dst, src + it * 4096, 4096, fb); bulk_ld(dst + 4096, src + 81920 + it * 4096, 4096, fb));
      src = P.sc->h2 + b * 196608;
#pragma unroll 1
      for (int it = 0; it < 24; it++) {
        if ((it & 7) == 0) { flag_wait(P.sc, F_H2 + it + (b >> 2), ep * 16); STAMP(55 + (it >> 3)); }
        if (it == G5AT) { flag_wait(P.sc, F_Y + b, ep * 4); STAMP(54); }
        if ((uint32_t)(it - G5AT) < 10) PSTEP(B_FF, 8192, bulk_ld(dst, P.sc->Y + b * 81920 + (it - G5AT) * 8192, 8192, fb));
        PSTEP(B_FM, 8192, bulk_ld(dst, src + it * 8192, 8192, fb));
      }
      PSTEP(B_FM, 20480, mbar_arrive(fb); tma_ld4(dst, &P.xa, fb, 64 * q, 0, 0, b); tma_ld4(dst + 16384, &P.xr, fb, 256 + 16 * q, 0, 0, b));
      src = P.sc->x1 + b * 81920;
      PSTEP(B_FM, 24576, mbar_arrive(fb); bulk_ld(dst, src + q * 8192, 8192, fb); bulk_ld(dst + 8192, src + (8 + (q >> 1)) * 4096, 4096, fb);
            bulk_ld(dst + 12288, src + 40960 + q * 8192, 8192, fb); bulk_ld(dst + 20480, src + (18 + (q >> 1)) * 4096, 4096, fb));
#undef PSTEP
    } else if (warp == 14) {
      nb_sync(NB_GO, 448);
      const bool el = elect();
      if (el) { bulk_st(P.sc->tab + slot * 6144, STG, 6144); bulk_commit(); bulk_wait_all(); flag_add(P.sc, F_TAB); }
      __syncwarp();
      STAMP(64);
      nb_arrive(NB_FREE, 288);
      mbar_wait(B_EP, 0);
      const uint32_t ep = lds_u32(EPO);
#pragma unroll 1
      for (int n = 0;; n++) {
        float4 v, u;
        asm volatile("ld.relaxed.gpu.global.v4.f32 {%0,%1,%2,%3}, [%4];" : "=f"(v.x), "=f"(v.y), "=f"(v.z), "=f"(v.w) : "l"(P.sc->row + b * 64 + lane) : "memory");
        asm volatile("ld.relaxed.gpu.global.v4.f32 {%0,%1,%2,%3}, [%4];" : "=f"(u.x), "=f"(u.y), "=f"(u.z), "=f"(u.w) : "l"(P.sc->row + b * 64 + 32 + lane) : "memory");
        if (__all_sync(~0u, __float_as_uint(v.w) == ep && __float_as_uint(u.w) == ep)) {
          sts_f4(ROW + lane * 16, v.x, v.y, v.z, v.w); sts_f4(ROW + 512 + lane * 16, u.x, u.y, u.z, u.w);
          break;
        }
        if (n > SPIN_MAX) __trap();
      }
      __syncwarp();
      if (el) mbar_arrive(B_ROW);
      STAMP(31);
      nb_arrive(NB_STATS, 416);
      l2_trickle(P, slot, lane, 0, 1);
#pragma unroll 1
      for (int jb = 0; jb < 5; jb++) {
        if (jb == 2) {
          flag_wait(P.sc, F_CS3, ep * 4);
          if (el) {
            mbar_expect(B_CS, 3072);
#pragma unroll 1
            for (int u = 0; u < 4; u++) bulk_ld(CSP + u * 768, P.sc->cs3 + u * 1536 + (2 * q + (b & 1)) * 192, 768, B_CS);
          }
          mbar_wait(B_CS, 0);
#pragma unroll 1
          for (int i = lane * 8; i < 768; i += 256) {
            const float2 a = lds_f2(CSP + i), c = lds_f2(CSP + 768 + i), d = lds_f2(CSP + 1536 + i), f = lds_f2(CSP + 2304 + i);
            sts_f2(CS3 + i, (a.x + c.x) + (d.x + f.x), (a.y + c.y) + (d.y + f.y));
          }
          STAMP(30);
          __syncwarp();
          nb_arrive(NB_CS3, 288);
        }
        const int bd = (b + (q & 2 ? 2 : 1) * (odd ? -1 : 1)) & 31;
        nb_sync(NB_RDY, 288);
        if (el) {
          if (jb < 2) bulk_st((jb ? P.sc->x1 + b * 81920 : P.sc->h + bd * 81920) + q * 20480, STG, 20480);
          else {
            unsigned char* d = P.sc->h2 + (b & ~1) * 196608 + (jb - 2) * 65536 + (2 * q + (b & 1)) * 8192;
            bulk_st(d, STG, 8192); bulk_st(d + 196608, STG + 8192, 8192);
          }
          if (jb == 1) bulk_st(P.sc->st1 + (b * 8 + q * 2) * 64, ST1, 1024);
          bulk_commit();
          if (jb > 2) { asm volatile("cp.async.bulk.wait_group 1;" ::: "memory"); flag_add(P.sc, F_H2 + 8 * (jb - 3) + (b >> 2)); }
          bulk_wait_read();
        }
        __syncwarp();
        nb_arrive(NB_FREE, 288);
        if (el && (jb < 2 || jb == 4)) { bulk_wait_all(); flag_add(P.sc, jb == 0 ? F_H + (bd >> 2) : jb == 1 ? F_X1 + (b >> 1) : F_H2 + 16 + (b >> 2)); }
        __syncwarp();
        STAMP(58 + jb);
        if (jb < 2) l2_trickle(P, slot, lane, 3 + jb, 4 + jb);
      }
      nb_sync(NB_RDY, 288);
      if (el) {
        tma_st4(&P.outa, STG, 64 * q, 0, 0, b); tma_st4(&P.outr, STG + 16384, 256 + 16 * q, 0, 0, b);
        bulk_commit(); bulk_wait_read();
      }
      __syncwarp();
      STAMP(63);
    } else {
      if ((uint32_t)__cvta_generic_to_shared(smem_raw) != SM) __trap();
      const uint32_t ep = ldg_u32(&P.sc->epoch[slot]) + 1;
      nb_sync(NB_INIT, 96);
      if (elect()) { P.sc->epoch[slot] = ep; sts_u32(EPO, ep); mbar_arrive(B_EP); }
      __syncwarp();
      STAMP(74);
      if (lane >= 3 && lane < 17) tmap_pf(&P.x + lane);
      l2_trickle(P, slot, lane, 1, 3);
      STAMP(28);
      const int k1 = slot >> 1, hh = slot & 1;
      const bool el = elect();
      nb_sync(NB_DMA, 160);
      if (el) {
        tma_st4(&P.t1a, FB, 0, 0, blkA, b); tma_st4(&P.t1h, FB + 16384, 0, 0, 5 * q + (odd ? 0 : 4), b);
        bulk_commit(); bulk_wait_read();
        mbar_expect(B_FFT, 21504);
        const int x0 = (k1 * 321 + 160 * hh) & ~7;
        tma_ld2(FB, &P.wr, B_FFT, x0, 0); tma_ld2(FB + 10752, &P.wi, B_FFT, x0, 0);
        bulk_wait_all(); flag_add(P.sc, F_T1 + (q >> 1));
      }
      __syncwarp();
      STAMP(75);
      flag_wait(P.sc, F_T1 + hh, ep * 64);
      STAMP(37);
      nb_sync(NB_DMA, 160);
      if (el) { mbar_expect(B_FFT, 20480); tma_ld3(FB, &P.t1l, B_FFT, 0, k1 * 32, 5 * hh); }
      nb_sync(NB_DMA, 160);
      if (el) { tma_st4(&P.t2s, FB, 0, 0, 5 * hh, k1); bulk_commit(); bulk_wait_all(); flag_add(P.sc, F_T2 + hh); }
      __syncwarp();
      STAMP(40);
      flag_wait(P.sc, F_T2 + (q >> 1), ep * 64);
      STAMP(41);
      if (el) {
        mbar_expect(B_FFT, (3 - odd) * 8192);
#pragma unroll 1
        for (int i = 0; i < 3 - odd; i++) tma_ld2(FB + i * 8192, &P.t2l, B_FFT, (blkA + i) * 64, b * 64);
      }
      nb_sync(NB_DMA, 160);
      if (el) { bulk_st(P.sc->Y + (b * 10 + blkA) * 8192, FB, (3 - odd) * 8192); bulk_commit(); bulk_wait_all(); flag_add(P.sc, F_Y + b); }
      __syncwarp();
      STAMP(44);
    }
  } else {
    if (slot >= 128) {
#pragma unroll 1
      for (int i = tid; i < 1600; i += 512) asm volatile("prefetch.global.L2 [%0];" ::"l"((const char*)P.pw1 + q * 204800 + i * 128));
      if (tid < 384 && 192 * q + (tid >> 1) < 640) asm volatile("prefetch.global.L2 [%0];" ::"l"(P.pw2 + (192 * q + (tid >> 1)) * 640 + 128 + 320 * (tid & 1)));
    }
    {
      const int g = slot < 128 ? slot * 384 + tid : 49152 + (slot - 128) * 512 + tid;
      const int inv = g >= 25600, R = (g - (inv ? 25600 : 0)) >> 3;
      const int tq = R / 800, Rq = R - 800 * tq;
      const int kc = inv ? Rq / 80 : Rq / 160, r = Rq - kc * (inv ? 80 : 160);
      const int k0 = 64 * kc + 8 * ((g & 7) ^ (r & 7));
      const int rr = (tq & 1) ? (r >= 128 ? r - 128 : r + 32) : r;
      const int kq = k0 / 160;
      const int mf = 160 * (tq >> 1) + (rr & ~1) + (tq & 1), m = mf ? mf : 320;
      const int d = r < 64 ? 64 * tq + r : 192 + 16 * tq + r;
      const int m2 = 160 * (kq >> 1) + (k0 - 160 * kq) + (kq & 1) + 4;
      int S = 2 * (inv ? d : m);
      const int base = ((inv ? m2 * d : (k0 + 4) * m + (rr & 1) * 160) + 320) % 640 - 320;
      S -= S > 320 ? 640 : 0;
      const float bs = (float)base, Sf = (float)S, H = inv ? 160.f : (float)m;
      uint32_t v[4];
#pragma unroll
      for (int e = 0; e < 4; e++) {
        float lo = fmaf((float)(e - 2), Sf, bs);
        if (e == 0 && inv && k0 == 0) lo = (float)((d & 1) * 320);
        v[e] = pack2(__cosf(lo * 0.009817477042468103f), __cosf((lo + H) * 0.009817477042468103f));
      }
      sts_u4((slot < 128 ? STG : HTB) + tid * 16, v[0], v[1], v[2], v[3]);
      fence_async_smem();
    }
    if (slot >= 128) {
      __syncthreads();
      helper_role(P, slot, warp, t_start);
    } else {
      nb_sync(NB_GO, 448);
      if (warp == 0) STAMP(0);
      if (warp >= 4) {
        asm volatile("setmaxnreg.inc.sync.aligned.u32 160;");
        mlp_role(P, b, q, warp >> 3, t_start);
      } else {
        asm volatile("setmaxnreg.inc.sync.aligned.u32 168;");
        fft_role(P, slot, warp & 3, t_start);
      }
    }
  }
}

typedef CUresult (*EncFn)(CUtensorMap*, CUtensorMapDataType, cuuint32_t, void*, const cuuint64_t*, const cuuint64_t*, const cuuint32_t*,
                          const cuuint32_t*, CUtensorMapInterleave, CUtensorMapSwizzle, CUtensorMapL2promotion, CUtensorMapFloatOOBfill);

static void enc(EncFn fn, CUtensorMap* m, const void* p, int rank, const cuuint64_t* dims, const cuuint64_t* strides, const cuuint32_t* box, int sw) {
  cuuint32_t es[5] = {1, 1, 1, 1, 1};
  fn(m, CU_TENSOR_MAP_DATA_TYPE_BFLOAT16, rank, (void*)p, dims, strides, box, es, CU_TENSOR_MAP_INTERLEAVE_NONE,
     sw == 128 ? CU_TENSOR_MAP_SWIZZLE_128B : sw == 32 ? CU_TENSOR_MAP_SWIZZLE_32B : CU_TENSOR_MAP_SWIZZLE_NONE, CU_TENSOR_MAP_L2_PROMOTION_L2_128B,
     CU_TENSOR_MAP_FLOAT_OOB_FILL_NONE);
}

extern "C" void kernel_launch(void* const* d_in, const int* in_sizes, int n_in, void* d_out, int out_size) {
  (void)in_sizes; (void)n_in; (void)out_size;
  void* fnp = nullptr;
  cudaDriverEntryPointQueryResult qr;
  cudaGetDriverEntryPoint("cuTensorMapEncodeTiled", &fnp, cudaEnableDefault, &qr);
  EncFn fn = (EncFn)fnp;
  Scratch* sc;
  cudaGetSymbolAddress((void**)&sc, g_sc);
  void *t1 = sc->T1, *t2 = sc->T2;

  Params P;
  P.sc = sc;
  P.px = (const __nv_bfloat16*)d_in[0]; P.pwr = (const __nv_bfloat16*)d_in[1]; P.pwi = (const __nv_bfloat16*)d_in[2];
  P.pw1 = (const __nv_bfloat16*)d_in[4]; P.pw2 = (const __nv_bfloat16*)d_in[5]; P.pw3 = (const __nv_bfloat16*)d_in[6]; P.pw4 = (const __nv_bfloat16*)d_in[7];
  { cuuint64_t d[3] = {640, 32, 64}, s[2] = {1280, 40960}; cuuint32_t bx[3] = {64, 1, 64}; enc(fn, &P.x, d_in[0], 3, d, s, bx, 128); }
  { cuuint64_t d[3] = {64, 640, 10}, s[2] = {1280, 128}; cuuint32_t bx[3] = {64, 64, 2}; enc(fn, &P.w1a, d_in[4], 3, d, s, bx, 128); enc(fn, &P.w2a, d_in[5], 3, d, s, bx, 128); }
  { cuuint64_t d[2] = {640, 640}, s[1] = {1280}; cuuint32_t bx[2] = {32, 32}; enc(fn, &P.w1b, d_in[4], 2, d, s, bx, 128); }
  { cuuint64_t d[3] = {320, 1536, 2}, s[2] = {1280, 640}; cuuint32_t bx[3] = {64, 64, 2}; enc(fn, &P.w4a, d_in[7], 3, d, s, bx, 128); }
  { cuuint64_t d[2] = {640, 640}, s[1] = {1280}; cuuint32_t bx[2] = {64, 64}; enc(fn, &P.w2h, d_in[5], 2, d, s, bx, 128); }
  { cuuint64_t d[2] = {640, 1536}, s[1] = {1280}; cuuint32_t bx[2] = {64, 64}; enc(fn, &P.w4h, d_in[7], 2, d, s, bx, 128); }
  { cuuint64_t d[2] = {20544, 32}, s[1] = {41088}; cuuint32_t bx[2] = {168, 32}; enc(fn, &P.wr, d_in[1], 2, d, s, bx, 0); enc(fn, &P.wi, d_in[2], 2, d, s, bx, 0); }
  { cuuint64_t d[3] = {64, 640, 24}, s[2] = {3072, 128}; cuuint32_t bx[3] = {64, 32, 3}; enc(fn, &P.w3, d_in[6], 3, d, s, bx, 128); }
  { cuuint64_t d[4] = {64, 64, 10, 32}, s[3] = {40960, 128, 1280}; cuuint32_t bx[4] = {64, 64, 2, 1}; enc(fn, &P.t1a, t1, 4, d, s, bx, 128); }
  { cuuint64_t d[4] = {32, 64, 20, 32}, s[3] = {40960, 64, 1280}; cuuint32_t bx[4] = {64, 64, 1, 1}; enc(fn, &P.t1h, t1, 4, d, s, bx, 128); }
  { cuuint64_t d[3] = {64, 2048, 10}, s[2] = {1280, 128}; cuuint32_t bx[3] = {64, 32, 5}; enc(fn, &P.t1l, t1, 3, d, s, bx, 128); }
  { cuuint64_t d[4] = {64, 32, 10, 64}, s[3] = {81920, 128, 1280}; cuuint32_t bx[4] = {64, 32, 5, 1}; enc(fn, &P.t2s, t2, 4, d, s, bx, 128); }
  { cuuint64_t d[2] = {640, 2048}, s[1] = {1280}; cuuint32_t bx[2] = {64, 64}; enc(fn, &P.t2l, t2, 2, d, s, bx, 128); }
  { cuuint64_t d[4] = {320, 64, 2, 32}, s[3] = {40960, 640, 1280}; cuuint32_t ba[4] = {64, 64, 2, 1}, br[4] = {16, 64, 2, 1};
    enc(fn, &P.outa, d_out, 4, d, s, ba, 128); enc(fn, &P.outr, d_out, 4, d, s, br, 32);
    enc(fn, &P.xa, d_in[0], 4, d, s, ba, 128); enc(fn, &P.xr, d_in[0], 4, d, s, br, 32); }

  cudaFuncSetAttribute(fused_kernel, cudaFuncAttributeMaxDynamicSharedMemorySize, SMEM_BYTES);
  fused_kernel<<<132, 512, SMEM_BYTES>>>(P);
}
```

```cpp
#include <cuda_runtime.h>
#include <cuda_bf16.h>
#include <cuda.h>
#include <stdint.h>
#include <stddef.h>

#define DEVI __device__ __forceinline__
#define NPRE_ 3

struct __align__(1024) Scratch {
  unsigned char tab[2 * 409600];
  unsigned char rem[34 * 16384];
  unsigned char h[32 * 20 * 4096];
  unsigned char x1[32 * 20 * 4096];
  unsigned char h2[32 * 48 * 4096];
  unsigned char Y[32 * 10 * 8192];
  __nv_bfloat16 T1[2048 * 640];
  __nv_bfloat16 T2[2048 * 640];
  float2 st1[32 * 8 * 64];
  float cs1[10 * 640];
  float cs3[4 * 1536];
  float4 row[2048];
  unsigned int flag[128 * 32];
  unsigned int epoch[160];
};
static_assert(offsetof(Scratch, x1) == offsetof(Scratch, h) + 2621440 && offsetof(Scratch, h2) == offsetof(Scratch, h) + 5242880, "layout");
__device__ Scratch g_sc;

enum { F_H = 0, F_X1 = 8, F_H2 = 16, F_Y = 48, F_TAB = 80, F_W2 = 81, F_W4 = 82, F_T1 = 83, F_T2 = 85, F_CS3 = 88, F_ST = 96 };

enum : uint32_t {
  NST = 6, SLOT = 28672, NPRE = NPRE_,
  SM = 1024,
  STG = SM + NST * SLOT,
  FB = STG + 24576,
  BAR = FB + 24576,
  ROW = BAR + 384,
  CS1 = ROW + 1024,
  CS3 = CS1 + 640,
  ST1 = CS3 + 768,
  DFR = ST1 + 1024,
  DF0 = STG + 22528,
  CSP = STG, STP = STG + 16384,
  EPO = DFR + 6144,
  PRF = EPO + 16,
  HTB = SM + 204800,
  SMEM_BYTES = PRF + 96 * 4 - SM,
  B_FM = BAR, B_FF = BAR + 48, B_EM = BAR + 96, B_G1 = BAR + 144, B_FFT = BAR + 152, B_ROW = BAR + 160, B_EP = BAR + 168, B_CS = BAR + 176,
  B_WT = BAR + 184,
  B_CSR = BAR + 232,
  B_U = BAR + 240, B_YD = BAR + 248,
  B_H2 = BAR + 256,
  NBAR = 38,
  H128 = 0x40000040u,
  H64 = 0x80000020u,
  SL16 = SLOT >> 4
};
enum { NB_WG2 = 1, NB_INIT = 2, NB_STATS = 3, NB_S = 4, NB_RDY = 5, NB_WG0 = 6, NB_T2 = 8, NB_GO = 10, NB_DMA = 11, NB_F1 = 12, NB_MLP = 13, NB_EP = 14, NB_TAB = 9 };
__device__ __forceinline__ int g1_chunk(int b, int it) { const int c = (b >> 2) + (b >> 4) + it; return c >= 10 ? c - 10 : c; }
__host__ __device__ constexpr uint32_t dlo(uint32_t addr, uint32_t lbo) { return (addr >> 4) | ((lbo >> 4) << 16); }

struct Params {
  Scratch* sc;
  const __nv_bfloat16 *px, *pwr, *pwi, *pw1, *pw2, *pw3, *pw4;
  CUtensorMap x, w1a, w1b, wr, wi, w3, t1a, t1h, t1l, t2s, t2l, outa, outr, w2a, w4a, w2h, w4h;
  int slot[132];
};

#define SPIN_MAX 4000000
#define G5C(j) ((0x26510 >> (4 * (j))) & 15)
#define FLAGA 5
#define T1GAP 500
#define T1FREE 2
DEVI void mbar_init(uint32_t b, int c) { asm volatile("mbarrier.init.shared::cta.b64 [%0], %1;" ::"r"(b), "r"(c)); }
DEVI void mbar_expect(uint32_t b, int bytes) { asm volatile("mbarrier.arrive.expect_tx.shared::cta.b64 _, [%0], %1;" ::"r"(b), "r"(bytes) : "memory"); }
DEVI void mbar_arrive(uint32_t b) { asm volatile("mbarrier.arrive.shared::cta.b64 _, [%0];" ::"r"(b) : "memory"); }
DEVI void mbar_arrive_n(uint32_t b, uint32_t n) { asm volatile("mbarrier.arrive.shared::cta.b64 _, [%0], %1;" ::"r"(b), "r"(n) : "memory"); }
DEVI void mbar_wait(uint32_t b, uint32_t par) {
  asm volatile("{\n.reg .pred p;\nL_%=:\nmbarrier.try_wait.parity.shared::cta.b64 p, [%0], %1;\n@!p bra.uni L_%=;\n}" ::"r"(b), "r"(par) : "memory");
}
DEVI bool elect() { uint32_t p; asm volatile("{\n.reg .pred P;\nelect.sync _|P, 0xffffffff;\nselp.u32 %0,1,0,P;\n}" : "=r"(p)); return p; }
DEVI void nb_sync(int id, int n) { asm volatile("bar.sync %0, %1;" ::"r"(id), "r"(n) : "memory"); }
DEVI void nb_arrive(int id, int n) { asm volatile("bar.arrive %0, %1;" ::"r"(id), "r"(n) : "memory"); }
DEVI void fence_async_smem() { asm volatile("fence.proxy.async.shared::cta;" ::: "memory"); }
DEVI void fence_async_gmem() { asm volatile("fence.proxy.async.global;" ::: "memory"); }
DEVI void bulk_ld(uint32_t dst, const void* src, int bytes, uint32_t bar) {
  asm volatile("cp.async.bulk.shared::cluster.global.mbarrier::complete_tx::bytes [%0], [%1], %2, [%3];" ::"r"(dst), "l"(src), "r"(bytes), "r"(bar) : "memory");
}
DEVI void bulk_st(void* dst, uint32_t src, int bytes) {
  asm volatile("cp.async.bulk.global.shared::cta.bulk_group [%0], [%1], %2;" ::"l"(dst), "r"(src), "r"(bytes) : "memory");
}
DEVI void tma_ld2(uint32_t dst, const CUtensorMap* m, uint32_t bar, int c0, int c1) {
  asm volatile("cp.async.bulk.tensor.2d.shared::cluster.global.mbarrier::complete_tx::bytes [%0], [%1, {%3, %4}], [%2];" ::"r"(dst), "l"(m), "r"(bar), "r"(c0), "r"(c1) : "memory");
}
DEVI void tma_ld3(uint32_t dst, const CUtensorMap* m, uint32_t bar, int c0, int c1, int c2) {
  asm volatile("cp.async.bulk.tensor.3d.shared::cluster.global.mbarrier::complete_tx::bytes [%0], [%1, {%3, %4, %5}], [%2];" ::"r"(dst), "l"(m), "r"(bar), "r"(c0), "r"(c1), "r"(c2) : "memory");
}
DEVI void tma_ld4(uint32_t dst, const CUtensorMap* m, uint32_t bar, int c0, int c1, int c2, int c3) {
  asm volatile("cp.async.bulk.tensor.4d.shared::cluster.global.mbarrier::complete_tx::bytes [%0], [%1, {%3, %4, %5, %6}], [%2];" ::"r"(dst), "l"(m), "r"(bar), "r"(c0), "r"(c1), "r"(c2), "r"(c3) : "memory");
}
DEVI void tma_st4(const CUtensorMap* m, uint32_t src, int c0, int c1, int c2, int c3) {
  asm volatile("cp.async.bulk.tensor.4d.global.shared::cta.bulk_group [%0, {%2, %3, %4, %5}], [%1];" ::"l"(m), "r"(src), "r"(c0), "r"(c1), "r"(c2), "r"(c3) : "memory");
}
DEVI void tmap_pf(const CUtensorMap* m) { asm volatile("prefetch.tensormap [%0];" ::"l"(m) : "memory"); }
DEVI void bulk_commit() { asm volatile("cp.async.bulk.commit_group;" ::: "memory"); }
DEVI void bulk_wait_read() { asm volatile("cp.async.bulk.wait_group.read 0;" ::: "memory"); }
DEVI void bulk_wait_all() { asm volatile("cp.async.bulk.wait_group 0;" ::: "memory"); }
#define SC(member, off) ((unsigned char*)P.sc + (uint32_t)(offsetof(Scratch, member) + (off)))
DEVI unsigned char* keep(unsigned char* p) { asm volatile("" : "+l"(p)); return p; }
DEVI unsigned char* flag_ptr(Scratch* sc, uint32_t f) { return (unsigned char*)sc + (uint32_t)(offsetof(Scratch, flag) + f * 128); }
DEVI void flag_add(Scratch* sc, uint32_t f) { asm volatile("red.relaxed.gpu.global.add.u32 [%0], 1;" ::"l"(flag_ptr(sc, f)) : "memory"); }
DEVI void flag_wait(Scratch* sc, uint32_t f, uint32_t target) {
  asm volatile("{\n.reg .pred p;\n.reg .u32 c, v;\nmov.u32 c, 0;\nL_%=:\nld.relaxed.gpu.global.u32 v, [%0];\nsub.u32 v, v, %1;\n"
               "setp.ge.s32 p, v, 0;\n@p bra.uni D_%=;\nadd.u32 c, c, 1;\nsetp.lt.u32 p, c, 4000000;\n@p bra.uni L_%=;\ntrap;\nD_%=:\n"
               "fence.proxy.async.global;\n}" ::"l"(flag_ptr(sc, f)), "r"(target) : "memory");
}
DEVI void watch(Scratch* sc, uint32_t f, uint32_t target, int k) { flag_wait(sc, f, target); if (elect()) mbar_arrive(B_WT + k * 8); __syncwarp(); }
DEVI void watched(int k) { mbar_wait(B_WT + k * 8, 0); fence_async_gmem(); }
DEVI void wg_fence() { asm volatile("wgmma.fence.sync.aligned;" ::: "memory"); }
DEVI void wg_commit() { asm volatile("wgmma.commit_group.sync.aligned;" ::: "memory"); }
template <int N> DEVI void wg_wait() { asm volatile("wgmma.wait_group.sync.aligned %0;" ::"n"(N) : "memory"); }
DEVI void stsm4(uint32_t a, uint32_t r0, uint32_t r1, uint32_t r2, uint32_t r3) {
  asm volatile("stmatrix.sync.aligned.m8n8.x4.shared.b16 [%0], {%1,%2,%3,%4};" ::"r"(a), "r"(r0), "r"(r1), "r"(r2), "r"(r3) : "memory");
}
DEVI void ldsm4(uint32_t a, uint32_t& r0, uint32_t& r1, uint32_t& r2, uint32_t& r3) {
  asm volatile("ldmatrix.sync.aligned.m8n8.x4.shared.b16 {%0,%1,%2,%3}, [%4];" : "=r"(r0), "=r"(r1), "=r"(r2), "=r"(r3) : "r"(a) : "memory");
}
DEVI uint32_t pack2(float lo, float hi) { uint32_t r; asm("cvt.rn.bf16x2.f32 %0, %1, %2;" : "=r"(r) : "f"(hi), "f"(lo)); return r; }
DEVI float bf_lo(uint32_t v) { return __uint_as_float(v << 16); }
DEVI float bf_hi(uint32_t v) { return __uint_as_float(v & 0xffff0000u); }
DEVI float2 lds_f2(uint32_t a) { float2 v; asm volatile("ld.shared.v2.f32 {%0,%1}, [%2];" : "=f"(v.x), "=f"(v.y) : "r"(a)); return v; }
DEVI float4 lds_f4(uint32_t a) { float4 v; asm volatile("ld.shared.v4.f32 {%0,%1,%2,%3}, [%4];" : "=f"(v.x), "=f"(v.y), "=f"(v.z), "=f"(v.w) : "r"(a)); return v; }
DEVI uint4 lds_u4(uint32_t a) { uint4 v; asm volatile("ld.shared.v4.u32 {%0,%1,%2,%3}, [%4];" : "=r"(v.x), "=r"(v.y), "=r"(v.z), "=r"(v.w) : "r"(a)); return v; }
DEVI uint32_t lds_u32(uint32_t a) { uint32_t v; asm volatile("ld.shared.u32 %0, [%1];" : "=r"(v) : "r"(a)); return v; }
DEVI void sts_u32(uint32_t a, uint32_t v) { asm volatile("st.shared.u32 [%0], %1;" ::"r"(a), "r"(v) : "memory"); }
DEVI void sts_f2(uint32_t a, float x, float y) { asm volatile("st.shared.v2.f32 [%0], {%1,%2};" ::"r"(a), "f"(x), "f"(y) : "memory"); }
DEVI void sts_f4(uint32_t a, float x, float y, float z, float w) { asm volatile("st.shared.v4.f32 [%0], {%1,%2,%3,%4};" ::"r"(a), "f"(x), "f"(y), "f"(z), "f"(w) : "memory"); }
DEVI void sts_u4(uint32_t a, uint32_t x, uint32_t y, uint32_t z, uint32_t w) { asm volatile("st.shared.v4.u32 [%0], {%1,%2,%3,%4};" ::"r"(a), "r"(x), "r"(y), "r"(z), "r"(w) : "memory"); }
DEVI uint32_t ldg_u32(const void* p) { uint32_t v; asm volatile("ld.global.u32 %0, [%1];" : "=r"(v) : "l"(p)); return v; }
DEVI uint32_t ldg_nc_u32(const void* p) { uint32_t v; asm volatile("ld.global.nc.u32 %0, [%1];" : "=r"(v) : "l"(p)); return v; }
DEVI uint32_t ldg_nc_u16(const void* p) { uint32_t v; asm volatile("ld.global.nc.u16 %0, [%1];" : "=r"(v) : "l"(p)); return v; }
DEVI uint4 ldg_nc_u4(const void* p) { uint4 v; asm volatile("ld.global.nc.v4.u32 {%0,%1,%2,%3}, [%4];" : "=r"(v.x), "=r"(v.y), "=r"(v.z), "=r"(v.w) : "l"(p)); return v; }
DEVI uint2 ldg_nc_u2(const void* p) { uint2 v; asm volatile("ld.global.nc.v2.u32 {%0,%1}, [%2];" : "=r"(v.x), "=r"(v.y) : "l"(p)); return v; }
DEVI float2 ldg_cg_f2(const void* p) { float2 v; asm volatile("ld.global.cg.v2.f32 {%0,%1}, [%2];" : "=f"(v.x), "=f"(v.y) : "l"(p)); return v; }
DEVI float tanh_fast(float x) { float y; asm("tanh.approx.f32 %0, %1;" : "=f"(y) : "f"(x)); return y; }
DEVI float silu(float v) { float hv = 0.5f * v; return fmaf(hv, tanh_fast(hv), hv); }

template <int N> DEVI void zero(float (&a)[N]) {
#pragma unroll
  for (int i = 0; i < N; i++) a[i] = 0.f;
}
template <int N> DEVI void pin(float (&a)[N]) {
#pragma unroll
  for (int i = 0; i < N; i++) asm volatile("" : "+f"(a[i])::"memory");
}
DEVI void pin1(uint32_t& v) { asm volatile("" : "+r"(v)::"memory"); }
DEVI uint32_t hadd2(uint32_t a, uint32_t b) { uint32_t r; asm("add.rn.bf16x2 %0, %1, %2;" : "=r"(r) : "r"(a), "r"(b)); return r; }
DEVI uint32_t hfma2(uint32_t a, uint32_t b, uint32_t c) { uint32_t r; asm("fma.rn.bf16x2 %0, %1, %2, %3;" : "=r"(r) : "r"(a), "r"(b), "r"(c)); return r; }
DEVI void landed(uint32_t v) { asm volatile("{\n.reg .pred p;\nsetp.eq.u32 p, %0, 0x7fc17fc1;\n@p st.shared.u32 [%1], %0;\n}" ::"r"(v), "r"(EPO + 8) : "memory"); }
DEVI void staged(uint32_t bar, int lane) { fence_async_smem(); __syncwarp(); if (lane == 0) mbar_arrive(bar); }
DEVI float rsq(float x) { float y; asm("rsqrt.approx.ftz.f32 %0, %1;" : "=f"(y) : "f"(x)); return y; }
DEVI void acc8(float (&c)[8], const uint4& v) {
  c[0] += bf_lo(v.x); c[1] += bf_hi(v.x); c[2] += bf_lo(v.y); c[3] += bf_hi(v.y);
  c[4] += bf_lo(v.z); c[5] += bf_hi(v.z); c[6] += bf_lo(v.w); c[7] += bf_hi(v.w);
}
template<int TB,uint32_t HA,uint32_t HB> DEVI void wg_ss_80(float (&d)[40], uint32_t a, uint32_t b, int sd){
  asm volatile("{\n.reg .b64 da, db;\n.reg .pred p;\nsetp.ne.b32 p, %45, 0;\nmov.b64 da, {%40, %42};\nmov.b64 db, {%41, %43};\nwgmma.mma_async.sync.aligned.m64n80k16.f32.bf16.bf16 {%0,%1,%2,%3,%4,%5,%6,%7,%8,%9,%10,%11,%12,%13,%14,%15,%16,%17,%18,%19,%20,%21,%22,%23,%24,%25,%26,%27,%28,%29,%30,%31,%32,%33,%34,%35,%36,%37,%38,%39}, da, db, p, 1, 1, 0, %44;\n}\n"
    : "+f"(d[0]),"+f"(d[1]),"+f"(d[2]),"+f"(d[3]),"+f"(d[4]),"+f"(d[5]),"+f"(d[6]),"+f"(d[7]),"+f"(d[8]),"+f"(d[9]),"+f"(d[10]),"+f"(d[11]),"+f"(d[12]),"+f"(d[13]),"+f"(d[14]),"+f"(d[15]),"+f"(d[16]),"+f"(d[17]),"+f"(d[18]),"+f"(d[19]),"+f"(d[20]),"+f"(d[21]),"+f"(d[22]),"+f"(d[23]),"+f"(d[24]),"+f"(d[25]),"+f"(d[26]),"+f"(d[27]),"+f"(d[28]),"+f"(d[29]),"+f"(d[30]),"+f"(d[31]),"+f"(d[32]),"+f"(d[33]),"+f"(d[34]),"+f"(d[35]),"+f"(d[36]),"+f"(d[37]),"+f"(d[38]),"+f"(d[39])
    : "r"(a), "r"(b), "n"(HA), "n"(HB), "n"(TB), "r"(sd));
}
template<int TB,uint32_t HA,uint32_t HB> DEVI void wg_ss_160(float (&d)[80], uint32_t a, uint32_t b, int sd){
  asm volatile("{\n.reg .b64 da, db;\n.reg .pred p;\nsetp.ne.b32 p, %85, 0;\nmov.b64 da, {%80, %82};\nmov.b64 db, {%81, %83};\nwgmma.mma_async.sync.aligned.m64n160k16.f32.bf16.bf16 {%0,%1,%2,%3,%4,%5,%6,%7,%8,%9,%10,%11,%12,%13,%14,%15,%16,%17,%18,%19,%20,%21,%22,%23,%24,%25,%26,%27,%28,%29,%30,%31,%32,%33,%34,%35,%36,%37,%38,%39,%40,%41,%42,%43,%44,%45,%46,%47,%48,%49,%50,%51,%52,%53,%54,%55,%56,%57,%58,%59,%60,%61,%62,%63,%64,%65,%66,%67,%68,%69,%70,%71,%72,%73,%74,%75,%76,%77,%78,%79}, da, db, p, 1, 1, 0, %84;\n}\n"
    : "+f"(d[0]),"+f"(d[1]),"+f"(d[2]),"+f"(d[3]),"+f"(d[4]),"+f"(d[5]),"+f"(d[6]),"+f"(d[7]),"+f"(d[8]),"+f"(d[9]),"+f"(d[10]),"+f"(d[11]),"+f"(d[12]),"+f"(d[13]),"+f"(d[14]),"+f"(d[15]),"+f"(d[16]),"+f"(d[17]),"+f"(d[18]),"+f"(d[19]),"+f"(d[20]),"+f"(d[21]),"+f"(d[22]),"+f"(d[23]),"+f"(d[24]),"+f"(d[25]),"+f"(d[26]),"+f"(d[27]),"+f"(d[28]),"+f"(d[29]),"+f"(d[30]),"+f"(d[31]),"+f"(d[32]),"+f"(d[33]),"+f"(d[34]),"+f"(d[35]),"+f"(d[36]),"+f"(d[37]),"+f"(d[38]),"+f"(d[39]),"+f"(d[40]),"+f"(d[41]),"+f"(d[42]),"+f"(d[43]),"+f"(d[44]),"+f"(d[45]),"+f"(d[46]),"+f"(d[47]),"+f"(d[48]),"+f"(d[49]),"+f"(d[50]),"+f"(d[51]),"+f"(d[52]),"+f"(d[53]),"+f"(d[54]),"+f"(d[55]),"+f"(d[56]),"+f"(d[57]),"+f"(d[58]),"+f"(d[59]),"+f"(d[60]),"+f"(d[61]),"+f"(d[62]),"+f"(d[63]),"+f"(d[64]),"+f"(d[65]),"+f"(d[66]),"+f"(d[67]),"+f"(d[68]),"+f"(d[69]),"+f"(d[70]),"+f"(d[71]),"+f"(d[72]),"+f"(d[73]),"+f"(d[74]),"+f"(d[75]),"+f"(d[76]),"+f"(d[77]),"+f"(d[78]),"+f"(d[79])
    : "r"(a), "r"(b), "n"(HA), "n"(HB), "n"(TB), "r"(sd));
}
template<int TB,uint32_t HA,uint32_t HB> DEVI void wg_ss_192(float (&d)[96], uint32_t a, uint32_t b, int sd){
  asm volatile("{\n.reg .b64 da, db;\n.reg .pred p;\nsetp.ne.b32 p, %101, 0;\nmov.b64 da, {%96, %98};\nmov.b64 db, {%97, %99};\nwgmma.mma_async.sync.aligned.m64n192k16.f32.bf16.bf16 {%0,%1,%2,%3,%4,%5,%6,%7,%8,%9,%10,%11,%12,%13,%14,%15,%16,%17,%18,%19,%20,%21,%22,%23,%24,%25,%26,%27,%28,%29,%30,%31,%32,%33,%34,%35,%36,%37,%38,%39,%40,%41,%42,%43,%44,%45,%46,%47,%48,%49,%50,%51,%52,%53,%54,%55,%56,%57,%58,%59,%60,%61,%62,%63,%64,%65,%66,%67,%68,%69,%70,%71,%72,%73,%74,%75,%76,%77,%78,%79,%80,%81,%82,%83,%84,%85,%86,%87,%88,%89,%90,%91,%92,%93,%94,%95}, da, db, p, 1, 1, 0, %100;\n}\n"
    : "+f"(d[0]),"+f"(d[1]),"+f"(d[2]),"+f"(d[3]),"+f"(d[4]),"+f"(d[5]),"+f"(d[6]),"+f"(d[7]),"+f"(d[8]),"+f"(d[9]),"+f"(d[10]),"+f"(d[11]),"+f"(d[12]),"+f"(d[13]),"+f"(d[14]),"+f"(d[15]),"+f"(d[16]),"+f"(d[17]),"+f"(d[18]),"+f"(d[19]),"+f"(d[20]),"+f"(d[21]),"+f"(d[22]),"+f"(d[23]),"+f"(d[24]),"+f"(d[25]),"+f"(d[26]),"+f"(d[27]),"+f"(d[28]),"+f"(d[29]),"+f"(d[30]),"+f"(d[31]),"+f"(d[32]),"+f"(d[33]),"+f"(d[34]),"+f"(d[35]),"+f"(d[36]),"+f"(d[37]),"+f"(d[38]),"+f"(d[39]),"+f"(d[40]),"+f"(d[41]),"+f"(d[42]),"+f"(d[43]),"+f"(d[44]),"+f"(d[45]),"+f"(d[46]),"+f"(d[47]),"+f"(d[48]),"+f"(d[49]),"+f"(d[50]),"+f"(d[51]),"+f"(d[52]),"+f"(d[53]),"+f"(d[54]),"+f"(d[55]),"+f"(d[56]),"+f"(d[57]),"+f"(d[58]),"+f"(d[59]),"+f"(d[60]),"+f"(d[61]),"+f"(d[62]),"+f"(d[63]),"+f"(d[64]),"+f"(d[65]),"+f"(d[66]),"+f"(d[67]),"+f"(d[68]),"+f"(d[69]),"+f"(d[70]),"+f"(d[71]),"+f"(d[72]),"+f"(d[73]),"+f"(d[74]),"+f"(d[75]),"+f"(d[76]),"+f"(d[77]),"+f"(d[78]),"+f"(d[79]),"+f"(d[80]),"+f"(d[81]),"+f"(d[82]),"+f"(d[83]),"+f"(d[84]),"+f"(d[85]),"+f"(d[86]),"+f"(d[87]),"+f"(d[88]),"+f"(d[89]),"+f"(d[90]),"+f"(d[91]),"+f"(d[92]),"+f"(d[93]),"+f"(d[94]),"+f"(d[95])
    : "r"(a), "r"(b), "n"(HA), "n"(HB), "n"(TB), "r"(sd));
}
template<int SD,int TB,uint32_t HB> DEVI void wg_rs_32(float (&d)[16], uint32_t a0, uint32_t a1, uint32_t a2, uint32_t a3, uint32_t b){
  asm volatile("{\n.reg .b64 db;\nmov.b64 db, {%20, %21};\nwgmma.mma_async.sync.aligned.m64n32k16.f32.bf16.bf16 {%0,%1,%2,%3,%4,%5,%6,%7,%8,%9,%10,%11,%12,%13,%14,%15}, {%16,%17,%18,%19}, db, %22, 1, 1, %23;\n}\n"
    : "+f"(d[0]),"+f"(d[1]),"+f"(d[2]),"+f"(d[3]),"+f"(d[4]),"+f"(d[5]),"+f"(d[6]),"+f"(d[7]),"+f"(d[8]),"+f"(d[9]),"+f"(d[10]),"+f"(d[11]),"+f"(d[12]),"+f"(d[13]),"+f"(d[14]),"+f"(d[15])
    : "r"(a0),"r"(a1),"r"(a2),"r"(a3), "r"(b), "n"(HB), "n"(SD), "n"(TB));
}
template<int SD,int TB,uint32_t HB> DEVI void wg_rs_64(float (&d)[32], uint32_t a0, uint32_t a1, uint32_t a2, uint32_t a3, uint32_t b){
  asm volatile("{\n.reg .b64 db;\nmov.b64 db, {%36, %37};\nwgmma.mma_async.sync.aligned.m64n64k16.f32.bf16.bf16 {%0,%1,%2,%3,%4,%5,%6,%7,%8,%9,%10,%11,%12,%13,%14,%15,%16,%17,%18,%19,%20,%21,%22,%23,%24,%25,%26,%27,%28,%29,%30,%31}, {%32,%33,%34,%35}, db, %38, 1, 1, %39;\n}\n"
    : "+f"(d[0]),"+f"(d[1]),"+f"(d[2]),"+f"(d[3]),"+f"(d[4]),"+f"(d[5]),"+f"(d[6]),"+f"(d[7]),"+f"(d[8]),"+f"(d[9]),"+f"(d[10]),"+f"(d[11]),"+f"(d[12]),"+f"(d[13]),"+f"(d[14]),"+f"(d[15]),"+f"(d[16]),"+f"(d[17]),"+f"(d[18]),"+f"(d[19]),"+f"(d[20]),"+f"(d[21]),"+f"(d[22]),"+f"(d[23]),"+f"(d[24]),"+f"(d[25]),"+f"(d[26]),"+f"(d[27]),"+f"(d[28]),"+f"(d[29]),"+f"(d[30]),"+f"(d[31])
    : "r"(a0),"r"(a1),"r"(a2),"r"(a3), "r"(b), "n"(HB), "n"(SD), "n"(TB));
}
template<int SD,int TB,uint32_t HB> DEVI void wg_rs_128(float (&d)[64], uint32_t a0, uint32_t a1, uint32_t a2, uint32_t a3, uint32_t b){
  asm volatile("{\n.reg .b64 db;\nmov.b64 db, {%68, %69};\nwgmma.mma_async.sync.aligned.m64n128k16.f32.bf16.bf16 {%0,%1,%2,%3,%4,%5,%6,%7,%8,%9,%10,%11,%12,%13,%14,%15,%16,%17,%18,%19,%20,%21,%22,%23,%24,%25,%26,%27,%28,%29,%30,%31,%32,%33,%34,%35,%36,%37,%38,%39,%40,%41,%42,%43,%44,%45,%46,%47,%48,%49,%50,%51,%52,%53,%54,%55,%56,%57,%58,%59,%60,%61,%62,%63}, {%64,%65,%66,%67}, db, %70, 1, 1, %71;\n}\n"
    : "+f"(d[0]),"+f"(d[1]),"+f"(d[2]),"+f"(d[3]),"+f"(d[4]),"+f"(d[5]),"+f"(d[6]),"+f"(d[7]),"+f"(d[8]),"+f"(d[9]),"+f"(d[10]),"+f"(d[11]),"+f"(d[12]),"+f"(d[13]),"+f"(d[14]),"+f"(d[15]),"+f"(d[16]),"+f"(d[17]),"+f"(d[18]),"+f"(d[19]),"+f"(d[20]),"+f"(d[21]),"+f"(d[22]),"+f"(d[23]),"+f"(d[24]),"+f"(d[25]),"+f"(d[26]),"+f"(d[27]),"+f"(d[28]),"+f"(d[29]),"+f"(d[30]),"+f"(d[31]),"+f"(d[32]),"+f"(d[33]),"+f"(d[34]),"+f"(d[35]),"+f"(d[36]),"+f"(d[37]),"+f"(d[38]),"+f"(d[39]),"+f"(d[40]),"+f"(d[41]),"+f"(d[42]),"+f"(d[43]),"+f"(d[44]),"+f"(d[45]),"+f"(d[46]),"+f"(d[47]),"+f"(d[48]),"+f"(d[49]),"+f"(d[50]),"+f"(d[51]),"+f"(d[52]),"+f"(d[53]),"+f"(d[54]),"+f"(d[55]),"+f"(d[56]),"+f"(d[57]),"+f"(d[58]),"+f"(d[59]),"+f"(d[60]),"+f"(d[61]),"+f"(d[62]),"+f"(d[63])
    : "r"(a0),"r"(a1),"r"(a2),"r"(a3), "r"(b), "n"(HB), "n"(SD), "n"(TB));
}
template<int SD,int TB,uint32_t HB> DEVI void wg_rs_160(float (&d)[80], uint32_t a0, uint32_t a1, uint32_t a2, uint32_t a3, uint32_t b){
  asm volatile("{\n.reg .b64 db;\nmov.b64 db, {%84, %85};\nwgmma.mma_async.sync.aligned.m64n160k16.f32.bf16.bf16 {%0,%1,%2,%3,%4,%5,%6,%7,%8,%9,%10,%11,%12,%13,%14,%15,%16,%17,%18,%19,%20,%21,%22,%23,%24,%25,%26,%27,%28,%29,%30,%31,%32,%33,%34,%35,%36,%37,%38,%39,%40,%41,%42,%43,%44,%45,%46,%47,%48,%49,%50,%51,%52,%53,%54,%55,%56,%57,%58,%59,%60,%61,%62,%63,%64,%65,%66,%67,%68,%69,%70,%71,%72,%73,%74,%75,%76,%77,%78,%79}, {%80,%81,%82,%83}, db, %86, 1, 1, %87;\n}\n"
    : "+f"(d[0]),"+f"(d[1]),"+f"(d[2]),"+f"(d[3]),"+f"(d[4]),"+f"(d[5]),"+f"(d[6]),"+f"(d[7]),"+f"(d[8]),"+f"(d[9]),"+f"(d[10]),"+f"(d[11]),"+f"(d[12]),"+f"(d[13]),"+f"(d[14]),"+f"(d[15]),"+f"(d[16]),"+f"(d[17]),"+f"(d[18]),"+f"(d[19]),"+f"(d[20]),"+f"(d[21]),"+f"(d[22]),"+f"(d[23]),"+f"(d[24]),"+f"(d[25]),"+f"(d[26]),"+f"(d[27]),"+f"(d[28]),"+f"(d[29]),"+f"(d[30]),"+f"(d[31]),"+f"(d[32]),"+f"(d[33]),"+f"(d[34]),"+f"(d[35]),"+f"(d[36]),"+f"(d[37]),"+f"(d[38]),"+f"(d[39]),"+f"(d[40]),"+f"(d[41]),"+f"(d[42]),"+f"(d[43]),"+f"(d[44]),"+f"(d[45]),"+f"(d[46]),"+f"(d[47]),"+f"(d[48]),"+f"(d[49]),"+f"(d[50]),"+f"(d[51]),"+f"(d[52]),"+f"(d[53]),"+f"(d[54]),"+f"(d[55]),"+f"(d[56]),"+f"(d[57]),"+f"(d[58]),"+f"(d[59]),"+f"(d[60]),"+f"(d[61]),"+f"(d[62]),"+f"(d[63]),"+f"(d[64]),"+f"(d[65]),"+f"(d[66]),"+f"(d[67]),"+f"(d[68]),"+f"(d[69]),"+f"(d[70]),"+f"(d[71]),"+f"(d[72]),"+f"(d[73]),"+f"(d[74]),"+f"(d[75]),"+f"(d[76]),"+f"(d[77]),"+f"(d[78]),"+f"(d[79])
    : "r"(a0),"r"(a1),"r"(a2),"r"(a3), "r"(b), "n"(HB), "n"(SD), "n"(TB));
}

#define STAMP(i)
#define STAMPW(i)
#define GSTAMP(i)

DEVI uint32_t sw64(uint32_t row, uint32_t c) { return row * 64 + ((c ^ ((row >> 1) & 3)) << 4); }
DEVI uint32_t sw128(uint32_t row, uint32_t c) { return row * 128 + ((c ^ (row & 7)) << 4); }

DEVI float gelu_s(float t, float k0, float k1, float hr) {
  const float h = t * hr;
  return fmaf(h, tanh_fast(t * fmaf(t * t, k1, k0)), h);
}
struct GeluK { float mu0, mu1, a0, a1, ah, b0, b1, bh; };
DEVI GeluK gelu_k(float mu0, float mu1, float rs0, float rs1) {
  return GeluK{mu0, mu1, 0.7978845608f * rs0, 0.0356774081f * rs0 * rs0 * rs0, 0.5f * rs0, 0.7978845608f * rs1, 0.0356774081f * rs1 * rs1 * rs1, 0.5f * rs1};
}
DEVI void gelu_unit(const float* a, const GeluK& k, float2 c, float2 d, uint32_t dst) {
  stsm4(dst, pack2(gelu_s(fmaf(-k.mu0, c.x, a[0]), k.a0, k.a1, k.ah), gelu_s(fmaf(-k.mu0, c.y, a[1]), k.a0, k.a1, k.ah)),
        pack2(gelu_s(fmaf(-k.mu1, c.x, a[2]), k.b0, k.b1, k.bh), gelu_s(fmaf(-k.mu1, c.y, a[3]), k.b0, k.b1, k.bh)),
        pack2(gelu_s(fmaf(-k.mu0, d.x, a[4]), k.a0, k.a1, k.ah), gelu_s(fmaf(-k.mu0, d.y, a[5]), k.a0, k.a1, k.ah)),
        pack2(gelu_s(fmaf(-k.mu1, d.x, a[6]), k.b0, k.b1, k.bh), gelu_s(fmaf(-k.mu1, d.y, a[7]), k.b0, k.b1, k.bh)));
}

DEVI void d_frags(uint32_t (&D)[8], int c0, int cs, int lane) {
#pragma unroll
  for (int i = 0; i < 4; i++) {
    const int v = c0 + cs * (8 * i + 2 * (lane & 3)) + 1024;
    const float a0 = (float)((v & 2047) - 1024) * 0.0030679615757712823f, a1 = (float)(((v + cs) & 2047) - 1024) * 0.0030679615757712823f;
    D[2 * i] = pack2(__cosf(a0), __cosf(a1)); D[2 * i + 1] = pack2(__sinf(a0), __sinf(a1));
  }
}

DEVI void fold(int b, int j, uint32_t row128, uint32_t sx, float mu0, float mu1, int odd) {
  const uint32_t dst = SM + (j ? j - 1 : 5) * SLOT + row128;
  const uint32_t oth = (j < 2 ? SM + 4 * SLOT + 8192 + j * 8192 : j == 2 ? FB + 16384 : j == 3 ? FB : SM + 4 * SLOT) + row128;
  const bool lo = g1_chunk(b, j) < 5;
  const uint32_t xa = lo ? oth : dst, xb = lo ? dst : oth;
  const float km = odd ? 0.f : -2.f;
  const uint32_t np0 = pack2(mu0 * km, mu0 * km), np1 = pack2(mu1 * km, mu1 * km), sg = odd ? 0xbf80bf80u : 0x3f803f80u;
  uint32_t u[16], v[16];
#pragma unroll
  for (int kk = 0; kk < 4; kk++) {
    ldsm4(xa + (sx ^ (kk << 5)), u[4 * kk], u[4 * kk + 1], u[4 * kk + 2], u[4 * kk + 3]);
    ldsm4(xb + (sx ^ (kk << 5)), v[4 * kk], v[4 * kk + 1], v[4 * kk + 2], v[4 * kk + 3]);
  }
#pragma unroll
  for (int kk = 0; kk < 4; kk++)
    stsm4(dst + (sx ^ (kk << 5)), hfma2(v[4 * kk], sg, hadd2(u[4 * kk], np0)), hfma2(v[4 * kk + 1], sg, hadd2(u[4 * kk + 1], np1)),
          hfma2(v[4 * kk + 2], sg, hadd2(u[4 * kk + 2], np0)), hfma2(v[4 * kk + 3], sg, hadd2(u[4 * kk + 3], np1)));
}

DEVI void mlp_role(const Params& P, int b, int q, int wg, int w, uint32_t t_start) {
  const int tid = threadIdx.x, lane = tid & 31;
  const int odd = q & 1;
  const int r0 = 16 * w + (lane >> 2);
  const int srow = 16 * w + (lane & 7) + ((lane >> 3) & 1) * 8;
  const int schk = lane >> 4;
  uint32_t phM = 0;
  uint32_t s = 0, sp = 0;
  const bool rel = (tid & 127) == 0;
#define STAGE_WAIT() mbar_wait(B_FM + s * 8, (phM >> s) & 1); phM ^= 1u << s; const uint32_t so = s * SL16; wg_fence();
#define STAGE_NEXT() wg_commit(); wg_wait<1>(); if (rel && it > 0) mbar_arrive(B_EM + sp * 8); sp = s; s = s == NST - 1 ? 0 : s + 1;
#define STAGE_END() wg_wait<0>(); if (rel) mbar_arrive(B_EM + sp * 8);

  const int ga = 2 * wg + odd, gs = odd ? 0 : 4;
  const uint32_t oA = sw64(srow, schk), oB = sw64(srow, 2 + schk);
  constexpr uint32_t dA = dlo(SM, 16);
  const uint32_t dBlo = dlo(SM + 8192, 16384) + wg * (dlo(8192, 0) - dlo(0, 8192 - 32));
  const uint32_t dBhi = dBlo + dlo(4096, 0) - dlo(0, 4096 - 64);
  float mu0, mu1;
  const uint32_t o128 = srow * 128, x128 = ((srow & 7) ^ schk) << 4;
  uint32_t wf[20], nr = 0, ni = 0;
  const int k1 = 2 * b + (q >> 1), k2 = 8 * w + (lane >> 2);
  const bool nyq = !odd && !wg && (lane & 3) == 0;
  uint32_t xf[20], yv[20];
#pragma unroll
  for (int i = 0; i < 20; i++) xf[i] = 0;
  {
    float acc[40];
    const uint32_t dB1 = dBlo + dlo(4096, FB - SM - 28672);
    STAMPW(80);
#pragma unroll 1
    for (int it = 0; it < 10; it++) {
      mbar_wait(B_FM + s * 8, (phM >> s) & 1); phM ^= 1u << s;
      const uint32_t so = s * SL16;
      if (it == 0) STAMPW(82);
      const int ck = g1_chunk(b, it);
      if (ck == q + 5 * wg) {
#pragma unroll
        for (int j = 0; j < 4; j++) ldsm4(SM + s * SLOT + o128 + (x128 ^ (j << 5)), xf[4 * j], xf[4 * j + 1], xf[4 * j + 2], xf[4 * j + 3]);
      }
      if (ck == 4 + 5 * wg) { ldsm4(SM + s * SLOT + o128 + (x128 ^ (q << 5)), xf[16], xf[17], xf[18], xf[19]); }
      const uint32_t dh = dB1 + so - s * dlo(0, SLOT - 4096);
      wg_fence();
#pragma unroll
      for (int kk = 0; kk < 4; kk++) wg_ss_80<1, H128, H128>(acc, dA + so + kk * 2, (kk < 2 ? dBlo + so : dh) + (kk & 1) * 128, kk ? 1 : it);
      STAGE_NEXT();
      landed(xf[0] ^ xf[4] ^ xf[8] ^ xf[12] ^ xf[16]);
    }
    wg_fence();
    STAGE_END();
    STAMPW(12); GSTAMP(16);
    const int carry = (b + (q & 2 ? 2 : 1) * (odd ? -1 : 1)) >> 5;
    const int drow = (srow + carry) & 63;
    const uint32_t dA_ = STG + sw64(drow, schk), dB_ = STG + sw64(drow, 2 + schk);
    nb_sync(NB_STATS, 416);
    const float4 s0 = lds_f4(ROW + r0 * 16), s1 = lds_f4(ROW + 128 + r0 * 16);
    mu0 = s0.x; mu1 = s1.x;
    const float rs0 = (r0 + carry < 0) ? 0.f : s0.z, rs1 = (r0 + 8 + carry >= 64) ? 0.f : s1.z;
    pin(acc);
    STAMPW(1);
    const GeluK gk = gelu_k(mu0, mu1, rs0, rs1);
    float2 cs[10];
#pragma unroll
    for (int j = 0; j < 10; j++) cs[j] = lds_f2(CS1 + (lane & 3) * 8 + (j < 8 ? ga * 128 + j * 32 : gs * 128 + wg * 64 + (j - 8) * 32));
#pragma unroll
    for (int j = 0; j < 5; j++) {
      gelu_unit(&acc[8 * j], gk, cs[2 * j], cs[2 * j + 1], j < 4 ? (ga + (j >> 1)) * 4096 + ((j & 1) ? dB_ : dA_) : gs * 4096 + (wg ? dB_ : dA_));
    }
    staged(B_H2, lane);
    STAMPW(2);
  }
  if (nyq) { const int o = (k1 + 64 * k2) * 321 + 320; nr = ldg_nc_u16(P.pwr + o); ni = ldg_nc_u16(P.pwi + o); }
  uint32_t E[16];
  {
    const int u = 32 * wg + k2;
    const float ng = (u & 1) ? -1.f : 1.f;
#pragma unroll
    for (int i = 0; i < 4; i++) {
      const int a = 8 * i + 2 * (lane & 3), v = u * a + 32;
      const float a0 = (float)((v & 63) - 32) * 0.09817477042468103f, a1 = (float)(((v + u) & 63) - 32) * 0.09817477042468103f;
      const float c0 = __cosf(a0), c1 = __cosf(a1), s0 = __sinf(a0), s1 = __sinf(a1);
      const float r0_ = __uint_as_float(lds_u32(ROW + 4 + a * 16)), r1_ = __uint_as_float(lds_u32(ROW + 20 + a * 16));
      const float r2_ = ng * __uint_as_float(lds_u32(ROW + 516 + a * 16)), r3_ = ng * __uint_as_float(lds_u32(ROW + 532 + a * 16));
      E[2 * i] = pack2(c0 * r0_, c1 * r1_); E[2 * i + 1] = pack2(s0 * r0_, s1 * r1_);
      E[8 + 2 * i] = pack2(c0 * r2_, c1 * r3_); E[9 + 2 * i] = pack2(s0 * r2_, s1 * r3_);
    }
    landed(E[0] ^ E[7] ^ E[9] ^ E[15]);
  }
    {
      const uint32_t a = STG + k2 * 336 + ((((k1 & 7) + wg) >> 1) + (lane & 3)) * 4, se = ((k1 ^ wg) & 1) ? 0x7632 : 0x5410;
      mbar_wait(B_CS, 0);
      STAMPW(77);
#pragma unroll
      for (int j = 0; j < 20; j++) {
        const uint32_t ad = a + j * 16 + (j < 16 ? wg * 64 : wg * -256);
        wf[j] = __byte_perm(lds_u32(ad), lds_u32(ad + 10752), se);
      }
      if (nyq) wf[0] = pack2(0.5f * bf_lo(nr), 0.5f * bf_lo(ni));
      landed(wf[19] ^ wf[18] ^ wf[15]);
      STAMPW(36);
    }
  {
    float acc[80];
    nb_sync(NB_F1, 384);
    wg_fence();
    wg_rs_160<0, 1, H128>(acc, E[0], E[1], E[2], E[3], dlo(FB, 8192));
    wg_rs_160<1, 1, H128>(acc, E[4], E[5], E[6], E[7], dlo(FB, 8192) + 128);
    wg_rs_160<1, 1, H128>(acc, E[8], E[9], E[10], E[11], dlo(FB, 8192) + 256);
    wg_rs_160<1, 1, H128>(acc, E[12], E[13], E[14], E[15], dlo(FB, 8192) + 384);
    wg_commit(); wg_wait<0>();
    pin(acc);
    uint32_t o[20];
#pragma unroll
    for (int i = 0; i < 20; i++) o[i] = pack2(acc[4 * i] + acc[4 * i + 3], acc[4 * i + 1] - acc[4 * i + 2]);
    nb_sync(NB_MLP, 256);
    const uint32_t vb = FB + (32 * wg + 8 * w + (lane & 7)) * 128, vx = ((lane & 7) ^ (lane >> 3)) << 4;
#pragma unroll
    for (int j = 0; j < 5; j++) stsm4(vb + (j >> 1) * 8192 + (vx ^ ((j & 1) << 6)), o[4 * j], o[4 * j + 1], o[4 * j + 2], o[4 * j + 3]);
    fence_async_smem();
    nb_arrive(NB_T2, 288);
    STAMPW(35);
  }
  s = 16 % NST;
  {
    float acc[40];
    const float ra = __uint_as_float(lds_u32(ROW + 4 + r0 * 16)), rb = __uint_as_float(lds_u32(ROW + 132 + r0 * 16));
#pragma unroll 1
    for (int it = 0; it < 10; it++) {
      STAGE_WAIT();
      if (it == 0) { STAMPW(3); GSTAMP(17); }
#pragma unroll
      for (int kk = 0; kk < 4; kk++) wg_ss_80<1, H64, H128>(acc, dA + so + (kk >> 1) * 256 + (kk & 1) * 2, (kk < 2 ? dBlo : dBhi) + so + (kk & 1) * 128, kk ? 1 : it);
      STAGE_NEXT();
    }
    STAGE_END();
    pin(acc);
    STAMPW(4); GSTAMP(18);
    const float n0 = -mu0 * ra, n1 = -mu1 * rb;
#pragma unroll
    for (int j = 0; j < 5; j++) {
#pragma unroll
      for (int f = 4 * j; f < 4 * j + 4; f++) {
        const float r_ = (f & 1) ? rb : ra, n_ = (f & 1) ? n1 : n0;
        yv[f] = pack2(fmaf(bf_lo(xf[f]), r_, n_) + acc[2 * f], fmaf(bf_hi(xf[f]), r_, n_) + acc[2 * f + 1]);
      }
      stsm4(STG + j * 4096 + (wg ? oB : oA), yv[4 * j], yv[4 * j + 1], yv[4 * j + 2], yv[4 * j + 3]);
    }
    staged(B_H2, lane);
    STAMPW(5);
    float s0 = 0.f, s1 = 0.f, v0 = 0.f, v1 = 0.f;
#pragma unroll
    for (int j = 0; j < 10; j++) {
      pin1(yv[2 * j]); pin1(yv[2 * j + 1]);
      const float a0 = bf_lo(yv[2 * j]), a1 = bf_hi(yv[2 * j]), a2 = bf_lo(yv[2 * j + 1]), a3 = bf_hi(yv[2 * j + 1]);
      s0 += a0 + a1; s1 += a2 + a3; v0 = fmaf(a0, a0, fmaf(a1, a1, v0)); v1 = fmaf(a2, a2, fmaf(a3, a3, v1));
    }
#pragma unroll
    for (int o = 1; o < 4; o <<= 1) {
      s0 += __shfl_xor_sync(~0u, s0, o); s1 += __shfl_xor_sync(~0u, s1, o); v0 += __shfl_xor_sync(~0u, v0, o); v1 += __shfl_xor_sync(~0u, v1, o);
    }
    if ((lane & 3) == 0) { sts_f2(ST1 + wg * 512 + r0 * 8, s0, v0); sts_f2(ST1 + 64 + wg * 512 + r0 * 8, s1, v1); }
    fence_async_smem();
    nb_arrive(NB_RDY, 288);
  }
  {
    const uint32_t dV = dlo(FB, 4096) + wg * 768;
    const uint32_t vb = FB + wg * 12288 + (8 * w + (lane & 7)) * 128, vx = ((lane & 7) ^ (lane >> 3)) << 4;
    mbar_wait(B_FFT, 0);
    STAMPW(38);
#pragma unroll
    for (int ps = 0; ps < 2; ps++) {
      float ac0[64], ac1[16];
      const uint4 d0 = lds_u4((ps ? DFR + 2048 : DF0) + (tid & 127) * 16), d1 = lds_u4(DFR + ps * 4096 + (tid & 127) * 16);
      const uint32_t D[8] = {d0.x, d0.y, d0.z, d0.w, d1.x, d1.y, d1.z, d1.w};
      wg_fence();
      wg_rs_128<0, 1, H128>(ac0, D[0], D[1], D[2], D[3], dV);
      wg_rs_128<1, 1, H128>(ac0, D[4], D[5], D[6], D[7], dV + 128);
      wg_rs_32<0, 1, H128>(ac1, D[0], D[1], D[2], D[3], dlo(FB + 8192, 4096) + wg * 4);
      wg_rs_32<1, 1, H128>(ac1, D[4], D[5], D[6], D[7], dlo(FB + 8192, 4096) + 128 + wg * 4);
      wg_commit(); wg_wait<0>();
      pin(ac0); pin(ac1);
      nb_sync(NB_WG0 + wg, 128);
#pragma unroll
      for (int j = 0; j < 5; j++) {
        uint32_t o[4];
#pragma unroll
        for (int u = 0; u < 4; u++) {
          const float* a = j < 4 ? &ac0[16 * j + 4 * u] : &ac1[4 * u];
          if (ps == 0) {
            const float xr = a[0] + a[3], xi = a[1] - a[2], wr = bf_lo(wf[4 * j + u]), wi = bf_hi(wf[4 * j + u]);
            o[u] = pack2(xr * wr - xi * wi, xr * wi + xi * wr);
          } else o[u] = pack2(a[0] - a[3], a[1] + a[2]);
        }
        stsm4(j < 4 ? vb + (j >> 1) * 4096 + (vx ^ ((j & 1) << 6)) : vb + 8192 - wg * 12288 + (vx ^ (wg << 6)), o[0], o[1], o[2], o[3]);
      }
      fence_async_smem();
      if (ps == 0) nb_sync(NB_WG0 + wg, 128);
    }
    STAMPW(39);
  }
  {
    float ac3[96];
    const uint32_t dA3 = dA + wg * 256;
    constexpr uint32_t dB = dlo(SM + 8192, 2048);
    mbar_wait(B_FM + s * 8, (phM >> s) & 1);
    nb_arrive(NB_T2, 288);
    STAMPW(6); GSTAMP(19);
    float m0, m1, rs0, rs1;
    float2 pa0, pa1, pb0, pb1;
    pa0.x = pa0.y = 0.f; pa1 = pb0 = pb1 = pa0;
#pragma unroll 1
    for (int it = 0; it < 20; it++) {
      STAGE_WAIT();
      wg_ss_192<1, H64, H128>(ac3, dA3 + so, dB + so, it);
      wg_ss_192<1, H64, H128>(ac3, dA3 + so + 2, dB + so + 384, 1);
      STAGE_NEXT();
      if (it == 18) {
        mbar_wait(B_ROW, 1);
        const uint32_t sa = STP + wg * 4096 + (lane & 3) * 1024 + r0 * 8;
        pa0 = lds_f2(sa); pa1 = lds_f2(sa + 512); pb0 = lds_f2(sa + 64); pb1 = lds_f2(sa + 576);
      }
    }
    m0 = pa0.x + pa1.x; m1 = pb0.x + pb1.x;
    float v0 = pa0.y + pa1.y, v1 = pb0.y + pb1.y;
#pragma unroll
    for (int o = 1; o < 4; o <<= 1) {
      m0 += __shfl_xor_sync(~0u, m0, o); m1 += __shfl_xor_sync(~0u, m1, o); v0 += __shfl_xor_sync(~0u, v0, o); v1 += __shfl_xor_sync(~0u, v1, o);
    }
    m0 *= 1.f / 640.f; m1 *= 1.f / 640.f;
    rs0 = rsq(fmaxf(fmaf(-m0, m0, v0 * (1.f / 640.f)), 0.f) + 1e-5f); rs1 = rsq(fmaxf(fmaf(-m1, m1, v1 * (1.f / 640.f)), 0.f) + 1e-5f);
    const GeluK gk = gelu_k(m0, m1, rs0, rs1);
    landed(__float_as_uint(gk.a1) ^ __float_as_uint(gk.b1));
    STAGE_END();
    STAMPW(7); GSTAMP(20);
    pin(ac3);
#pragma unroll 1
    for (int r = 0; r < 2; r++) {
      float2 cs[12];
#pragma unroll
      for (int j = 0; j < 4; j++) cs[j] = lds_f2(CS3 + r * 384 + j * 32 + (lane & 3) * 8);
#pragma unroll
      for (int h = 0; h < 3; h++) {
        const uint32_t buf = STG + r * 24576 + h * 8192 + wg * 4096;
        if (h < 2) {
#pragma unroll
          for (int j = 4 * h + 4; j < 4 * h + 8; j++) cs[j] = lds_f2(CS3 + r * 384 + j * 32 + (lane & 3) * 8);
        }
        if (h == 2) mbar_wait(B_H2, 0);
        gelu_unit(&ac3[16 * h], gk, cs[4 * h], cs[4 * h + 1], buf + oA);
        gelu_unit(&ac3[16 * h + 8], gk, cs[4 * h + 2], cs[4 * h + 3], buf + oB);
        staged(B_H2 + (3 * r + h) * 8, lane);
      }
      if (r) break;
#pragma unroll
      for (int i = 0; i < 48; i++) ac3[i] = ac3[i + 48];
      mbar_wait(B_YD, 0);
    }
    STAMPW(8);
  }
  {
  float acc[40];
#pragma unroll 1
  for (int it = 0; it < 24; it++) {
    STAGE_WAIT();
    if (it == 0) { STAMPW(9); GSTAMP(21); }
#pragma unroll
    for (int kk = 0; kk < 4; kk++) wg_ss_80<1, H64, H128>(acc, dA + so + (kk >> 1) * 256 + (kk & 1) * 2, (kk < 2 ? dBlo : dBhi) + so + (kk & 1) * 128, kk ? 1 : it);
    STAGE_NEXT();
  }
  STAGE_END();
  pin(acc);
#pragma unroll
  for (int i = 0; i < 20; i++) { asm volatile("mov.b32 %0, %0;" : "+r"(xf[i])); asm volatile("mov.b32 %0, %0;" : "+r"(yv[i])); }
  STAMPW(10); GSTAMP(22);
#pragma unroll
  for (int f = 0; f < 20; f++) { acc[2 * f] = silu(bf_lo(yv[f]) + acc[2 * f]); acc[2 * f + 1] = silu(bf_hi(yv[f]) + acc[2 * f + 1]); }
  {
    float z = 0.f;
#pragma unroll
    for (int f = 0; f < 40; f += 2) z = fmaf(acc[f], acc[f + 1], z);
    landed(__float_as_uint(z));
  }
  STAMPW(13);
  nb_sync(NB_S, 384);
  STAMPW(14);
#pragma unroll
  for (int j = 0; j < 5; j++) {
    uint32_t sv[4], o[4];
    const uint32_t ot = j < 4 ? wg * 8192 + o128 + (x128 ^ (j << 5)) : 16384 + wg * 2048 + srow * 32 + ((schk ^ ((srow >> 2) & 1)) << 4);
    ldsm4(FB + (j < 4 ? ot : 16384 + o128 + (x128 ^ (wg << 5))), sv[0], sv[1], sv[2], sv[3]);
#pragma unroll
    for (int u = 0; u < 4; u++) {
      const int f = 4 * j + u;
      o[u] = pack2(fmaf(bf_lo(sv[u]), acc[2 * f], bf_lo(xf[f])), fmaf(bf_hi(sv[u]), acc[2 * f + 1], bf_hi(xf[f])));
    }
    stsm4(STG + ot, o[0], o[1], o[2], o[3]);
  }
  fence_async_smem();
  nb_arrive(NB_RDY, 288);
  STAMPW(11); GSTAMP(23);
  }
#undef STAGE_WAIT
#undef STAGE_NEXT
#undef STAGE_END
}

DEVI void e_frags(uint32_t (&Cf)[16], uint32_t (&Sf)[16], int r0, int lane) {
  const float sc = 2.f / (2048.f * 640.f);
  const uint32_t sneg = 0x80008000u;
#pragma unroll
  for (int i = 0; i < 4; i++) {
    const int row = r0 + 8 * (i & 1), i0 = row * (8 * (i >> 1) + 2 * (lane & 3)) + 32;
    const float a0 = (float)((i0 & 63) - 32) * 0.09817477042468103f, a1 = (float)(((i0 + row) & 63) - 32) * 0.09817477042468103f;
    Cf[i] = pack2(sc * __cosf(a0), sc * __cosf(a1)); Sf[i] = pack2(sc * __sinf(a0), sc * __sinf(a1));
  }
  const bool sw = r0 & 1;
  const uint32_t N = 0x80008000u, m1 = sw ? N : 0u;
  const uint32_t nc = ((r0 + 1) & 2) ? N : 0u, ns = ((r0 & 2) ? N : 0u) ^ sneg;
#pragma unroll
  for (int i = 0; i < 4; i++) {
    Cf[4 + i] = (sw ? Sf[i] : Cf[i]) ^ nc; Sf[4 + i] = (sw ? Cf[i] : Sf[i]) ^ ns;
    Sf[i] ^= sneg;
    Cf[8 + i] = Cf[i] ^ m1; Sf[8 + i] = Sf[i] ^ m1; Cf[12 + i] = Cf[4 + i] ^ m1; Sf[12 + i] = Sf[4 + i] ^ m1;
  }
}
DEVI void s_step(const uint32_t (&Cf)[16], const uint32_t (&Sf)[16], int na, uint32_t sbase, uint32_t sx) {
#pragma unroll 1
  for (int i = 0; i < na; i++) {
    const uint32_t dU = dlo(FB, 8192) + i * 512;
    float p[32], r[32];
    wg_fence();
    wg_rs_64<0, 1, H128>(p, Cf[0], Cf[1], Cf[2], Cf[3], dU);
    wg_rs_64<0, 1, H128>(r, Sf[0], Sf[1], Sf[2], Sf[3], dU);
#pragma unroll
    for (int kk = 1; kk < 4; kk++) {
      wg_rs_64<1, 1, H128>(p, Cf[4 * kk], Cf[4 * kk + 1], Cf[4 * kk + 2], Cf[4 * kk + 3], dU + kk * 128);
      wg_rs_64<1, 1, H128>(r, Sf[4 * kk], Sf[4 * kk + 1], Sf[4 * kk + 2], Sf[4 * kk + 3], dU + kk * 128);
    }
    wg_commit(); wg_wait<0>();
    pin(p); pin(r);
    nb_sync(NB_WG2, 128);
#pragma unroll
    for (int j = 0; j < 4; j++) {
      uint32_t o[4];
#pragma unroll
      for (int u = 0; u < 4; u++) { const int f = 2 * (4 * j + u); o[u] = pack2(p[f] + r[f + 1], p[f + 1] - r[f]); }
      stsm4(sbase + i * 8192 + (sx ^ (j << 5)), o[0], o[1], o[2], o[3]);
    }
  }
  fence_async_smem();
  nb_arrive(NB_DMA, 160);
}

DEVI void fft_role(const Params& P, int slot, int w, uint32_t t_start) {
  const int b = slot >> 2, q = slot & 3, odd = q & 1;
  const int t = threadIdx.x & 127, lane = t & 31;
  const int r0 = 16 * w + (lane >> 2);
  const int srow = 16 * w + (lane & 7) + ((lane >> 3) & 1) * 8;
  const uint32_t sbase = FB + srow * 128, sx = ((srow & 7) ^ (lane >> 4)) << 4;

  uint32_t ep;
  {
    const __nv_bfloat16* p = P.px + (32 * (16 * q + (t >> 3)) + b) * 640 + 8 * (t & 7);
    uint4 ev[10];
    STAMPW(50);
    const int c0 = g1_chunk(b, 0);
    p += c0 * 64;
#pragma unroll
    for (int i = 0; i < 10; i++) { if (i + c0 == 10) p -= 640; ev[i] = ldg_nc_u4(p + i * 64); }
    {
      const int pc = min(t >> 3, 9), it = pc >= 5, rg = t & 7;
      const int cc = 5 * (b & 3) + pc - 5 * it;
      const uint32_t b0 = (cc < 16 ? SM + it * SLOT + 8192 + (cc >> 3) * 8192 : SM + it * SLOT + 24576) + sw128(rg, cc & 7);
      const uint32_t b1 = cc < 16 ? b0 + 4096 : FB + it * 4096 + sw128(rg, cc & 7);
      float c8[8];
      zero(c8);
      if (w < 3) {
        mbar_wait(B_FM + (w ? 8 : 0), 0);
        if (w == 1) mbar_wait(B_FM, 0);
#pragma unroll 1
        for (int hf = 0; hf < 2; hf++) {
#pragma unroll
          for (int i = 0; i < 4; i++) acc8(c8, lds_u4((hf ? b1 : b0) + i * 1024));
        }
        landed(__float_as_uint(c8[0]));
        if (lane == 0) mbar_arrive(B_CSR);
      }
#pragma unroll
      for (int i = 0; i < 4; i++) { const bool up = lane & 4; const float o = __shfl_xor_sync(~0u, up ? c8[i] : c8[i + 4], 4); c8[i] = (up ? c8[i + 4] : c8[i]) + o; }
#pragma unroll
      for (int i = 0; i < 2; i++) { const bool up = lane & 2; const float o = __shfl_xor_sync(~0u, up ? c8[i] : c8[i + 2], 2); c8[i] = (up ? c8[i + 2] : c8[i]) + o; }
      { const bool up = lane & 1; const float o = __shfl_xor_sync(~0u, up ? c8[0] : c8[1], 1); c8[0] = (up ? c8[1] : c8[0]) + o; }
      const int col = 160 * q + 8 * (odd ? (cc >= 16 ? cc - 16 : cc + 4) : cc) + rg;
      mbar_wait(B_EP, 0);
      ep = lds_u32(EPO);
      if (t < ((b & 12) == 12 ? 80 : 40))
        asm volatile("st.relaxed.gpu.global.u32 [%0], %1;" ::"l"(SC(cs1, (g1_chunk(b, it) * 640 + col) * 4)), "r"((__float_as_uint(c8[0]) & ~1u) | (ep & 1)) : "memory");
      __syncwarp();
    }
    STAMPW(32);
    float c[4], d[4];
    zero(c); zero(d);
#pragma unroll 1
    for (int hf = 0; hf < 2; hf++) {
#pragma unroll
      for (int i = 0; i < 5; i++) {
        const uint32_t e[4] = {ev[i].x, ev[i].y, ev[i].z, ev[i].w};
#pragma unroll
        for (int k = 0; k < 4; k++) {
          const float lo = bf_lo(e[k]), hi = bf_hi(e[k]);
          c[k] += lo + hi; d[k] = fmaf(lo, lo, fmaf(hi, hi, d[k]));
        }
        ev[i] = ev[i + 5];
      }
    }
    float a = (c[0] + c[1]) + (c[2] + c[3]), g = (d[0] + d[1]) + (d[2] + d[3]);
#pragma unroll
    for (int o = 1; o < 8; o <<= 1) { a += __shfl_xor_sync(~0u, a, o); g += __shfl_xor_sync(~0u, g, o); }
    const float m = a * (1.f / 640.f), var = fmaxf(fmaf(-m, m, g * (1.f / 640.f)), 0.f), r1 = rsq(var + 1e-5f);
    if ((t & 7) == 0)
      asm volatile("st.relaxed.gpu.global.v4.f32 [%0], {%1,%2,%3,%4};" ::"l"(SC(row, (slot * 16 + (t >> 3)) * 16)), "f"(m), "f"(r1),
                   "f"(r1 * rsq(var * r1 * r1 + 1e-5f)), "f"(__uint_as_float(ep)) : "memory");
    __syncwarp();
    STAMPW(78);
  }
  {
    {
      {
        const float* csp = (const float*)SC(cs1, 640 * q + 8 * min(t, 79));
        float x, y;
        int n = 0;
        bool again;
#pragma unroll 1
        do {
          uint2 cp[10];
#pragma unroll
          for (int k = 0; k < 10; k++) asm volatile("ld.relaxed.gpu.global.v2.u32 {%0,%1}, [%2];" : "=r"(cp[k].x), "=r"(cp[k].y) : "l"(csp + k * 640) : "memory");
          uint32_t o = 0, a = ~0u;
          x = y = 0.f;
#pragma unroll
          for (int k = 0; k < 10; k++) { o |= cp[k].x | cp[k].y; a &= cp[k].x & cp[k].y; x += __uint_as_float(cp[k].x); y += __uint_as_float(cp[k].y); }
          again = __any_sync(~0u, ((o ^ ep) | (a ^ ep)) & 1);
        } while (again && ++n < SPIN_MAX);
        if (again) __trap();
        if (t < 80) sts_f2(CS1 + t * 8, x, y);
        __syncwarp();
        nb_arrive(NB_STATS, 416);
        STAMPW(29);
      }
      mbar_wait(B_ROW, 0);
      const float mu0 = __uint_as_float(lds_u32(ROW + r0 * 16)), mu1 = __uint_as_float(lds_u32(ROW + 128 + r0 * 16));
      mbar_wait(B_FF + 4 * 8, 0);
#pragma unroll 1
      for (int j = 0; j < 5; j++) {
        mbar_wait(B_EM + (j ? j - 1 : 5) * 8, j > 0);
        if (j == 2 || j == 3) mbar_wait(B_FF + (j == 2 ? 5 : 1) * 8, 0);
        if (j == 0) STAMPW(66);
        fold(b, j, srow * 128, sx, mu0, mu1, odd);
      }
      fence_async_smem();
      float acc[80];
      nb_sync(NB_WG2, 128);
      STAMPW(33);
      uint32_t s = 5, sp = 4;
#pragma unroll 1
      for (int it = 0; it < 5; it++) {
        const uint32_t a = dlo(SM, 16) + s * SL16;
        mbar_wait(B_FF + s * 8, 0);
        wg_fence();
#pragma unroll
        for (int kk = 0; kk < 4; kk++) wg_ss_160<0, H128, H128>(acc, a + 2 * kk, a + 512 + 2 * kk, kk ? 1 : it);
        wg_commit();
        wg_wait<1>();
        if (t == 0) mbar_arrive_n(B_EM + sp * 8, 2);
        sp = s; s = s == NST - 1 ? 0 : s + 1;
      }
      wg_wait<0>();
      if (t == 0) mbar_arrive_n(B_EM + 3 * 8, 2);
      pin(acc);
      STAMPW(34);
#pragma unroll
      for (int j = 0; j < 10; j++) {
        const float* a = &acc[j * 8];
        stsm4(sbase + (j >> 2) * 8192 + (sx ^ ((j & 3) << 5)), pack2(a[0], a[1]), pack2(a[2], a[3]), pack2(a[4], a[5]), pack2(a[6], a[7]));
      }
      fence_async_smem();
      nb_arrive(NB_F1, 384);
      STAMPW(76);
    }
  }
  {
    const int k1 = slot >> 1, u = 8 * w + (lane >> 2);
#pragma unroll 1
    for (int ps = 0; ps < 2; ps++) {
      uint32_t D[8];
      d_frags(D, ps ? u * k1 : 0, ps ? 64 * u : k1 + 64 * u, lane);
      sts_u4((ps ? DFR + 2048 : DF0) + t * 16, D[0], D[1], D[2], D[3]); sts_u4(DFR + ps * 4096 + t * 16, D[4], D[5], D[6], D[7]);
    }
    __syncwarp();
    if (lane == 0) mbar_arrive(B_FFT);
  }
  {
    uint32_t Cf[16], Sf[16];
    e_frags(Cf, Sf, r0, lane);
    mbar_wait(B_U, 0);
    STAMPW(42);
    s_step(Cf, Sf, 3 - odd, sbase, sx);
    STAMPW(43);
  }
  {
    float p[40], r[40];
    uint32_t s = 70 % NST;
#pragma unroll 1
    for (int j = 0; j < 5; j++) {
      const uint32_t a0 = dlo(SM, 16) + s * SL16, a1 = dlo(STG, 16) + j * 512, b0 = a0 + 512, b1 = b0 + 640;
      const uint32_t ap = j < 4 ? a0 + 4 : a1, bp = j < 4 ? b0 + 4 : b1, aq = j < 4 ? a1 : a0 + 4, bq = j < 4 ? b1 : b0 + 4;
      mbar_wait(B_FF + s * 8, 1);
      wg_fence();
      wg_ss_80<0, H128, H128>(p, a0, b0, j); wg_ss_80<0, H128, H128>(p, a0 + 2, b0 + 2, 1);
      wg_ss_80<0, H128, H128>(p, ap, bp, 1); wg_ss_80<0, H128, H128>(p, ap + 2, bp + 2, 1);
      wg_ss_80<0, H128, H128>(r, aq, bq, j); wg_ss_80<0, H128, H128>(r, aq + 2, bq + 2, 1);
      wg_ss_80<0, H128, H128>(r, a1 + 4, b1 + 4, 1); wg_ss_80<0, H128, H128>(r, a1 + 6, b1 + 6, 1);
      wg_commit();
      s = s == NST - 1 ? 0 : s + 1;
    }
    wg_wait<0>();
    nb_sync(NB_WG2, 128);
    pin(p); pin(r);
    STAMPW(45);
#pragma unroll
    for (int j = 0; j < 5; j++) {
      uint32_t o0[4], o1[4];
#pragma unroll
      for (int u = 0; u < 4; u++) {
        const int f = 8 * j + 2 * u;
        o0[u] = pack2(p[f] + r[f], p[f + 1] + r[f + 1]); o1[u] = pack2(p[f] - r[f], p[f + 1] - r[f + 1]);
      }
      stsm4(sbase + (j < 4 ? (sx ^ (j << 5)) : 16384 + sx), o0[0], o0[1], o0[2], o0[3]);
      stsm4(sbase + (j < 4 ? 8192 + (sx ^ (j << 5)) : 16384 + (sx ^ 32)), o1[0], o1[1], o1[2], o1[3]);
    }
  }
  nb_arrive(NB_S, 384);
}

DEVI void helper_role(const Params& P, int slot, int warp, uint32_t t_start) {
  const int tid = threadIdx.x, q = slot & 3;
  const int n2 = q == 3 ? 1 : 3;
  if (warp == 15) {
    uint32_t ep = 0;
    if (elect()) { bulk_st(SC(tab, 786432 + q * 8192), HTB, 8192); bulk_commit(); }
#pragma unroll 1
    for (int j = 0; j < 17; j++) {
      const int d = j == 1 ? 0 : j > 4 ? j - 4 : -1;
      if (d >= 0) nb_sync(3, 416);
      if (elect()) {
        if (d == 0 || d >= 11) { bulk_st(SC(rem, (d ? 6 * q + 3 * d - 23 : 3 * q) * 16384), SM + (d & 3) * 49152, (d ? 3 : n2) * 16384); bulk_commit(); }
        if (d == 10) { bulk_st(SC(cs3, q * 6144), HTB, 6144); bulk_commit(); }
        if (j == 4 || d == 10 || d == 12) { bulk_wait_all(); flag_add(P.sc, j == 4 ? F_W2 : d == 10 ? F_CS3 : F_W4); }
        if (j < 13) {
          const uint32_t mb = BAR + (j & 3) * 8, buf = SM + (j & 3) * 49152;
          mbar_arrive(mb); mbar_expect(mb, j ? 49152 : n2 * 16384);
          if (j == 0 || j > 10) {
#pragma unroll 1
            for (int u = 0; u < (j ? 3 : n2); u++) {
              const int t = 6 * q + 3 * (j - 11) + u;
              const int row = j ? 192 * (t & 7) + 64 * (t >> 3) : 64 * (3 * q + u);
              tma_ld2(buf + u * 16384, j ? &P.w4h : &P.w2h, mb, 256, row); tma_ld2(buf + u * 16384 + 8192, j ? &P.w4h : &P.w2h, mb, 576, row);
            }
          } else bulk_ld(buf, (const unsigned char*)P.pw3 + q * 491520 + (j - 1) * 49152, 49152, mb);
        }
        if (j == 0) { bulk_wait_all(); flag_add(P.sc, F_TAB); }
      }
      __syncwarp();
    }
    ep = ldg_u32(&P.sc->epoch[slot]) + 1;
    __syncwarp();
    if (elect()) P.sc->epoch[slot] = ep;
    flag_wait(P.sc, F_TAB, ep * 132);
    return;
  }
  if (warp >= 12) return;
  float c[8];
  zero(c);
  const uint32_t mo = ((tid >= 192 ? 7 * 192 : 0) + tid) * 16;
#pragma unroll 1
  for (int j = 0; j < 13; j++) {
    const uint32_t buf = SM + (j & 3) * 49152;
    mbar_wait(BAR + (j & 3) * 8, (j >> 2) & 1);
    if (j == 0 || j > 10) {
      const uint32_t bs = buf + (tid >> 7) * 16384;
      const int k0 = (tid & 127) >> 3, cc = tid & 7;
      uint4 v[8];
#pragma unroll
      for (int u = 0; u < 8; u++) v[u] = lds_u4(bs + (u & 1) * 8192 + sw128(k0 + 16 * (u >> 1), cc));
      landed(v[0].x ^ v[1].x ^ v[2].x ^ v[3].x ^ v[4].x ^ v[5].x ^ v[6].x ^ v[7].x);
      nb_sync(5, 384);
#pragma unroll
      for (int u = 0; u < 8; u++)
        sts_u4(bs + (cc >> 1) * 4096 + sw128(k0 + 16 * ((u >> 1) & 1), (u >> 2) * 4 + 2 * (u & 1) + (cc & 1)), v[u].x, v[u].y, v[u].z, v[u].w);
    } else {
#pragma unroll
      for (int i = 0; i < 8; i++) acc8(c, lds_u4(buf + mo + i * 3072));
      landed(__float_as_uint(c[0]));
      if (j == 10) {
        if (tid >= 192) { sts_f4(HTB + (tid - 192) * 32, c[0], c[1], c[2], c[3]); sts_f4(HTB + (tid - 192) * 32 + 16, c[4], c[5], c[6], c[7]); }
        nb_sync(5, 384);
        if (tid < 192) {
          const float4 a = lds_f4(HTB + tid * 32), d = lds_f4(HTB + tid * 32 + 16);
          sts_f4(HTB + tid * 32, c[0] + a.x, c[1] + a.y, c[2] + a.z, c[3] + a.w); sts_f4(HTB + tid * 32 + 16, c[4] + d.x, c[5] + d.y, c[6] + d.z, c[7] + d.w);
        }
      }
    }
    fence_async_smem();
    nb_sync(3, 416);
  }
}

DEVI void l2_trickle(const void* p, int n, int slot, int lane) {
  const char* a = (const char*)p + (uint32_t)(slot * n);
#pragma unroll 1
  for (int o = 0; o < n; o += 4096) { asm volatile("prefetch.global.L2 [%0];" ::"l"(a + (uint32_t)min(o + lane * 128, n - 1))); __nanosleep(100); }
}

template <int I0, int I1> DEVI void init_barriers() {
#pragma unroll
  for (int i = I0; i < I1; i++) mbar_init(BAR + i * 8, BAR + i * 8 < B_G1 ? 2 : BAR + i * 8 == B_CSR ? 3 : BAR + i * 8 == B_FFT ? 5 : BAR + i * 8 >= B_H2 ? 8 : 1);
  asm volatile("fence.mbarrier_init.release.cluster;" ::: "memory");
}

__global__ void __launch_bounds__(512, 1) fused_kernel(const __grid_constant__ Params P) {
  extern __shared__ __align__(1024) unsigned char smem_raw[];
  const int tid = threadIdx.x, lane = tid & 31;
  const int warp = __shfl_sync(~0u, tid >> 5, 0);
  const uint32_t t_start = 0;
  uint32_t nsm, smid;
  asm volatile("mov.u32 %0, %%nsmid;" : "=r"(nsm));
  asm volatile("mov.u32 %0, %%smid;" : "=r"(smid));
  const int ts = P.slot[min(smid, 131u)], slot = nsm == 132 ? ts : blockIdx.x;
  const int b = slot >> 2, q = slot & 3, odd = q & 1;

  const int blkA = (5 * q + 1) >> 1, colS = 160 * q + (odd ? 0 : 128);
  if (warp == 14 && elect()) { tmap_pf(&P.x); tmap_pf(&P.w1a); tmap_pf(&P.w1b); }
  if (warp == 12 && slot < 128) {
    STAMP(24);
    if (elect()) init_barriers<0, NPRE>();
    __syncwarp();
    nb_arrive(NB_GO, 448);
    if (elect()) {
#pragma unroll 1
      for (int it = 0; it < NPRE; it++) {
        const uint32_t dst = SM + it * SLOT, fb = B_FM + it * 8;
        mbar_arrive(fb); mbar_expect(fb, 28672);
        const int k0 = g1_chunk(b, it) * 64;
        tma_ld3(dst, &P.x, fb, k0, b, 0);
        tma_ld3(dst + 8192, &P.w1a, fb, 0, k0, blkA); tma_ld2(dst + 24576, &P.w1b, fb, colS, k0); tma_ld2(FB + it * 4096, &P.w1b, fb, colS, k0 + 32);
      }
    }
    __syncwarp();
    STAMP(72);
  }
  if (warp == 13 && slot < 128) {
    if (elect()) init_barriers<NPRE, NBAR>();
    __syncwarp();
    nb_arrive(NB_GO, 448); nb_arrive(NB_EP, 64);
    STAMP(46);
  }
  if (warp < 12 || slot >= 128) {
    {
      const int g = slot < 128 ? slot * 384 + tid : 49152 + (slot - 128) * 512 + tid;
      const int inv = g >= 25600, R = (g - (inv ? 25600 : 0)) >> 3;
      const int tq = R / 800, Rq = R - 800 * tq;
      const int kc = inv ? Rq / 80 : Rq / 160, r = Rq - kc * (inv ? 80 : 160);
      const int k0 = 64 * kc + 8 * ((g & 7) ^ (r & 7));
      const int rr = (tq & 1) ? (r >= 128 ? r - 128 : r + 32) : r;
      const int kq = k0 / 160;
      const int mf = 160 * (tq >> 1) + (rr & ~1) + (tq & 1), m = mf ? mf : 320;
      const int d = r < 64 ? 64 * tq + r : 192 + 16 * tq + r;
      const int m2 = 160 * (kq >> 1) + (k0 - 160 * kq) + (kq & 1) + 4;
      int S = 2 * (inv ? d : m);
      const int base = ((inv ? m2 * d : (k0 + 4) * m + (rr & 1) * 160) + 320) % 640 - 320;
      S -= S > 320 ? 640 : 0;
      const float bs = (float)base, Sf = (float)S, H = inv ? 160.f : (float)m;
      uint32_t v[4];
#pragma unroll
      for (int e = 0; e < 4; e++) {
        float lo = fmaf((float)(e - 2), Sf, bs);
        if (e == 0 && inv && k0 == 0) lo = (float)((d & 1) * 320);
        v[e] = pack2(__cosf(lo * 0.009817477042468103f), __cosf((lo + H) * 0.009817477042468103f));
      }
      sts_u4((slot < 128 ? STG : HTB) + tid * 16, v[0], v[1], v[2], v[3]);
      STAMP(27);
      fence_async_smem();
    }
  }
  if (warp < 12 || slot >= 128) {
    if (slot >= 128) {
      if (tid == 0) init_barriers<0, 8>();
      __syncthreads();
      helper_role(P, slot, warp, t_start);
    } else {
      nb_sync(NB_GO, 448);
      nb_arrive(NB_TAB, 416);
      if (warp == 0) STAMP(0);
      if (warp >= 4) {
        asm volatile("setmaxnreg.inc.sync.aligned.u32 176;");
        mlp_role(P, b, q, warp >> 3, warp & 3, t_start);
      } else {
        asm volatile("setmaxnreg.inc.sync.aligned.u32 136;");
        fft_role(P, slot, warp & 3, t_start);
      }
    }
  } else {
    asm volatile("setmaxnreg.dec.sync.aligned.u32 24;");
    uint32_t s = NPRE, ph = 1;
#define PSTEP(FULL_, bytes, ISSUE) { mbar_wait(B_EM + s * 8, ph); const uint32_t dst = SM + s * SLOT, fb = FULL_ + s * 8; \
      if (elect()) { mbar_expect(fb, bytes); ISSUE; } __syncwarp(); if (++s == NST) { s = 0; ph ^= 1; } }
    if (warp == 14) {
      STAMP(49);
      nb_sync(NB_TAB, 416);
      if (elect()) { bulk_st(SC(tab, slot * 6144), STG, 6144); bulk_commit(); bulk_wait_all(); flag_add(P.sc, F_TAB); }
      __syncwarp();
      STAMP(64);
      mbar_wait(B_EP, 0);
      const uint32_t ep = lds_u32(EPO);
      {
        float4 v, u;
        int n = 0;
        bool ok;
        const unsigned char* rp = SC(row, (b * 64 + lane) * 16);
#pragma unroll 1
        do {
          asm volatile("ld.relaxed.gpu.global.v4.f32 {%0,%1,%2,%3}, [%4];" : "=f"(v.x), "=f"(v.y), "=f"(v.z), "=f"(v.w) : "l"(rp) : "memory");
          asm volatile("ld.relaxed.gpu.global.v4.f32 {%0,%1,%2,%3}, [%4+512];" : "=f"(u.x), "=f"(u.y), "=f"(u.z), "=f"(u.w) : "l"(rp) : "memory");
          ok = __all_sync(~0u, __float_as_uint(v.w) == ep && __float_as_uint(u.w) == ep);
        } while (!ok && ++n < SPIN_MAX);
        if (!ok) __trap();
        sts_f4(ROW + lane * 16, v.x, v.y, v.z, v.w); sts_f4(ROW + 512 + lane * 16, u.x, u.y, u.z, u.w);
      }
      __syncwarp();
      if (elect()) mbar_arrive(B_ROW);
      STAMP(31);
      nb_arrive(NB_STATS, 416);
      l2_trickle(P.pw2, 6400, slot, lane);
#pragma unroll 1
      for (int jb = 0; jb < 2; jb++) {
        const int bd = (b + (q & 2 ? 2 : 1) * (odd ? -1 : 1)) & 31;
        unsigned char* d = keep(SC(h, (jb ? 2621440 + b * 81920 : bd * 81920) + q * 20480));
        mbar_wait(B_H2, jb);
        if (elect()) {
          bulk_st(d, STG, 20480);
          bulk_commit();
          if (jb == 0) {
            bulk_wait_read();
            mbar_expect(B_CS, 21504);
            const int x0 = ((slot >> 1) * 321 + 160 * (slot & 1)) & ~7;
            tma_ld2(STG, &P.wr, B_CS, x0, 0); tma_ld2(STG + 10752, &P.wi, B_CS, x0, 0);
          }
          bulk_wait_all();
          flag_add(P.sc, jb ? F_X1 + (b >> 2) : F_H + (bd >> 2));
        }
        __syncwarp();
        STAMP(58 + jb);
        if (jb) {
          nb_sync(NB_RDY, 288);
          if (elect()) { bulk_st(SC(st1, slot * 1024), ST1, 1024); bulk_commit(); bulk_wait_all(); flag_add(P.sc, F_ST + (b >> 1)); }
          __syncwarp();
        }
        if (jb == 0) { mbar_wait(B_CS, 0); l2_trickle(P.pw4, 15360, slot, lane); }
      }
      flag_wait(P.sc, F_ST + (b >> 1), ep * 8);
      flag_wait(P.sc, F_CS3, ep * 4);
      mbar_wait(B_G1, 1);
      if (elect()) {
        mbar_expect(B_CS, 3072 + 8192);
        bulk_ld(STP, SC(st1, (b & ~1) * 4096), 8192, B_CS);
#pragma unroll 1
        for (int u = 0; u < 4; u++) bulk_ld(CSP + u * 768, SC(cs3, u * 6144 + (2 * q + (b & 1)) * 768), 768, B_CS);
      }
      mbar_wait(B_CS, 1);
#pragma unroll 1
      for (int i0 = 0; i0 < 768; i0 += 256) {
        const int i = i0 + lane * 8;
        const float2 a = lds_f2(CSP + i), c = lds_f2(CSP + 768 + i), d = lds_f2(CSP + 1536 + i), f = lds_f2(CSP + 2304 + i);
        sts_f2(CS3 + i, (a.x + c.x) + (d.x + f.x), (a.y + c.y) + (d.y + f.y));
      }
      STAMP(30);
      __syncwarp();
      if (elect()) mbar_arrive(B_ROW);
      __syncwarp();
      watch(P.sc, F_W4, ep * 4, 2);
#pragma unroll 1
      for (int j = 0; j < 6; j++) {
        unsigned char* d = keep(SC(h2, (b & ~1) * 196608 + (j >> 1) * 65536 + (2 * q + (b & 1)) * 8192 + (j & 1) * 4096));
        mbar_wait(B_H2 + j * 8, 0);
        if (elect()) {
          bulk_st(d, STG + j * 8192, 4096); bulk_st(d + 196608, STG + j * 8192 + 4096, 4096);
          bulk_commit();
          if (j == FLAGA) { asm volatile("cp.async.bulk.wait_group %0;" ::"n"(FLAGA - 1) : "memory"); flag_add(P.sc, F_H2 + (b >> 2)); }
        }
        __syncwarp();
        if (j == 0) STAMP(79);
        if (j == FLAGA) STAMP(60);
      }
      if (elect()) { bulk_wait_all(); flag_add(P.sc, F_H2 + 8 + (b >> 2)); }
      __syncwarp();
      STAMP(62);
      watch(P.sc, F_H2 + 8 + (b >> 2), ep * 16, 3);
      nb_sync(NB_RDY, 288);
      if (elect()) {
        tma_st4(&P.outa, STG, 64 * q, 0, 0, b); tma_st4(&P.outr, STG + 16384, 256 + 16 * q, 0, 0, b);
        bulk_commit(); bulk_wait_read();
      }
      __syncwarp();
      STAMP(63);
    } else if (warp == 15) {
      if ((uint32_t)__cvta_generic_to_shared(smem_raw) != SM) __trap();
      const uint32_t ep = ldg_u32(SC(epoch, slot * 4)) + 1;
      nb_sync(NB_EP, 64);
      if (elect()) { *(uint32_t*)SC(epoch, slot * 4) = ep; sts_u32(EPO, ep); mbar_arrive(B_EP); }
      __syncwarp();
      STAMP(74);
#pragma unroll 1
      for (int i = 3; i < 15; i++) tmap_pf(&P.x + i);
      watch(P.sc, F_TAB, ep * 132, 0);
      mbar_wait(B_FM + 5 * 8, 0);
#pragma unroll 1
      for (int a = 0; a < 3; a++) l2_trickle(a == 2 ? P.pw3 : a ? P.pwi : P.pwr, a == 2 ? 15360 : 10272, slot, lane);
      STAMP(28);
      watch(P.sc, F_W2, ep * 4, 1);
      const int k1 = slot >> 1, hh = slot & 1;
      nb_sync(NB_T2, 288);
      if (elect()) {
        tma_st4(&P.t1h, FB + 16384, 0, 0, 5 * q + (odd ? 0 : 4), b);
#pragma unroll 1
        for (int i = 0; i < 4; i++) {
          const uint32_t t0 = (uint32_t)clock64();
          while (i >= T1FREE && (uint32_t)clock64() - t0 < T1GAP) {}
          tma_st4(&P.t1a, FB + i * 4096, 0, 32 * (i & 1), blkA + (i >> 1), b);
        }
        bulk_commit();
        bulk_wait_all(); flag_add(P.sc, F_T1 + (q >> 1));
      }
      __syncwarp();
      STAMP(75);
      flag_wait(P.sc, F_T1 + hh, ep * 64);
      STAMP(37);
      if (elect()) { mbar_expect(B_FFT, 20480); tma_ld3(FB, &P.t1l, B_FFT, 0, k1 * 32, 5 * hh); }
      nb_sync(NB_T2, 288);
      if (elect()) { tma_st4(&P.t2s, FB, 0, 0, 5 * hh, k1); bulk_commit(); bulk_wait_all(); flag_add(P.sc, F_T2 + hh); mbar_arrive(B_G1); }
      __syncwarp();
      STAMP(40);
      flag_wait(P.sc, F_T2 + (q >> 1), ep * 64);
      STAMP(41);
      if (elect()) {
        mbar_expect(B_U, (3 - odd) * 8192);
#pragma unroll 1
        for (int i = 0; i < 3 - odd; i++) tma_ld2(FB + i * 8192, &P.t2l, B_U, (blkA + i) * 64, b * 64);
      }
      unsigned char* yd = keep(SC(Y, (b * 10 + blkA) * 8192));
      nb_sync(NB_DMA, 160);
      if (elect()) { bulk_st(yd, FB, (3 - odd) * 8192); bulk_commit(); bulk_wait_all(); flag_add(P.sc, F_Y + (b >> 2)); mbar_arrive(B_YD); }
      __syncwarp();
      STAMP(44);
      watch(P.sc, F_Y + (b >> 2), ep * 16, 4);
      STAMP(54);
    } else if (warp == 13) {
      nb_sync(NB_INIT, 64);
#pragma unroll 1
      for (int it = NPRE; it < 10; it++) PSTEP(B_FM, 8192, tma_ld3(dst, &P.x, fb, g1_chunk(b, it) * 64, b, 0));
      PSTEP(B_FF, 16384, mbar_arrive(fb); tma_ld3(dst + 8192, &P.x, fb, g1_chunk(b, 0) * 64, b, 0); tma_ld3(dst + 16384, &P.x, fb, g1_chunk(b, 1) * 64, b, 0));
#pragma unroll 1
      for (int it = 0; it < 5; it++)
        PSTEP(B_FF, (it & 5) ? 0 : 8192, (void)dst; if (!(it & 5)) tma_ld3(FB + (s - 1) * 4096, &P.x, fb, g1_chunk(b, 2 + (it >> 1)) * 64, b, 0));
      mbar_wait(B_EP, 0);
      const uint32_t ep = lds_u32(EPO);
#pragma unroll 1
      for (int g = 0; g < 3; g++) {
        const unsigned char* src = SC(h, g == 0 ? b * 81920 : g == 1 ? 2621440 + (b & ~1) * 81920 : 5242880 + b * 196608);
        const int n = g == 0 ? 10 : g == 1 ? 20 : 24, step = g == 1 ? 4096 : 8192, o2 = g == 1 ? 81920 : 4096;
        flag_wait(P.sc, F_H + 8 * g + (b >> 2), ep * 16);
        if (g == 0 && elect()) mbar_arrive(B_G1);
        __syncwarp();
        STAMP(g == 2 ? 55 : 52 + g);
#pragma unroll 1
        for (int it = 0; it < n; it++) {
          if (g == 2 && it == 8) watched(3);
          PSTEP(B_FM, 8192, bulk_ld(dst, src, 4096, fb); bulk_ld(dst + 4096, src + o2, 4096, fb));
          src += step;
        }
      }
      const unsigned char* src = SC(Y, b * 81920);
      watched(4);
#pragma unroll 1
      for (int it = 0; it < 5; it++) PSTEP(B_FF, 16384, bulk_ld(dst, src + G5C(it) * 8192, 8192, fb); bulk_ld(STG + it * 8192, src + (G5C(it) + (it < 4 ? 3 : 5)) * 8192, 8192, fb));
    } else {
      nb_sync(NB_INIT, 64);
#pragma unroll 1
      for (int it = NPRE; it < 10; it++) {
        const int k0 = g1_chunk(b, it) * 64;
        if (it == NST) mbar_wait(B_CSR, 0);
        PSTEP(B_FM, 20480, tma_ld3(dst + 8192, &P.w1a, fb, 0, k0, blkA); tma_ld2(dst + 24576, &P.w1b, fb, colS, k0); tma_ld2(FB + s * 4096, &P.w1b, fb, colS, k0 + 32));
        if (it == 5) STAMP(73);
      }
      s = 5;
#pragma unroll 1
      for (int g = 0; g < 2; g++) {
        if (g == 0) watched(0);
        else {
#pragma unroll 1
          for (int m = 0; m < 2; m++) {
            watched(1 + m);
            if (m == 0) mbar_wait(B_G1, 0);
            const unsigned char* rem = SC(rem, q * 4096 + m * 163840);
#pragma unroll 1
            for (int it = 0; it < (m ? 24 : 10); it++) {
              PSTEP(B_FM, 20480, tma_ld3(dst + 8192, &P.w2a + m, fb, 64 * q, m ? 192 * (it & 7) + 64 * (it >> 3) : 64 * it, 0); bulk_ld(dst + 24576, rem, 4096, fb));
              rem += 16384;
            }
#pragma unroll 1
            for (int it = 0; it < (m ? 0 : 20); it++) {
              const int gr = it / 5, j = it - 5 * gr;
              PSTEP(B_FM, 12288, tma_ld4(dst + 8192, &P.w3, fb, 0, j < 4 ? 64 * gr + 16 * j : 256 + 16 * gr, 6 * q + 3 * (b & 1), 0));
            }
          }
        }
#pragma unroll 1
        for (int it = 0; it < 5; it++) {
          const int c = g1_chunk(b, it);
          const unsigned char* tp = SC(tab, q * 102400 + (g ? 40 + G5C(it) : c >= 5 ? 2 * c - 10 : 2 * c) * 10240);
          PSTEP(B_FF, 20480, bulk_ld(dst + 8192, tp, 10240, fb); bulk_ld(dst + 18432, tp + (g ? (it < 4 ? 3 : 5) : 1) * 10240, 10240, fb));
        }
      }
    }
#undef PSTEP
  }
}

typedef CUresult (*EncFn)(CUtensorMap*, CUtensorMapDataType, cuuint32_t, void*, const cuuint64_t*, const cuuint64_t*, const cuuint32_t*,
                          const cuuint32_t*, CUtensorMapInterleave, CUtensorMapSwizzle, CUtensorMapL2promotion, CUtensorMapFloatOOBfill);

static void enc(EncFn fn, CUtensorMap* m, const void* p, int rank, const cuuint64_t* dims, const cuuint64_t* strides, const cuuint32_t* box, int sw) {
  cuuint32_t es[5] = {1, 1, 1, 1, 1};
  fn(m, CU_TENSOR_MAP_DATA_TYPE_BFLOAT16, rank, (void*)p, dims, strides, box, es, CU_TENSOR_MAP_INTERLEAVE_NONE,
     sw == 128 ? CU_TENSOR_MAP_SWIZZLE_128B : sw == 32 ? CU_TENSOR_MAP_SWIZZLE_32B : CU_TENSOR_MAP_SWIZZLE_NONE, CU_TENSOR_MAP_L2_PROMOTION_L2_128B,
     CU_TENSOR_MAP_FLOAT_OOB_FILL_NONE);
}

extern "C" void kernel_launch(void* const* d_in, const int* in_sizes, int n_in, void* d_out, int out_size) {
  (void)in_sizes; (void)n_in; (void)out_size;
  void* fnp = nullptr;
  cudaDriverEntryPointQueryResult qr;
  cudaGetDriverEntryPoint("cuTensorMapEncodeTiled", &fnp, cudaEnableDefault, &qr);
  EncFn fn = (EncFn)fnp;
  Scratch* sc;
  cudaGetSymbolAddress((void**)&sc, g_sc);
  void *t1 = sc->T1, *t2 = sc->T2;

  Params P;
  P.sc = sc;
  P.px = (const __nv_bfloat16*)d_in[0]; P.pwr = (const __nv_bfloat16*)d_in[1]; P.pwi = (const __nv_bfloat16*)d_in[2];
  P.pw1 = (const __nv_bfloat16*)d_in[4]; P.pw2 = (const __nv_bfloat16*)d_in[5]; P.pw3 = (const __nv_bfloat16*)d_in[6]; P.pw4 = (const __nv_bfloat16*)d_in[7];
  { cuuint64_t d[3] = {640, 32, 64}, s[2] = {1280, 40960}; cuuint32_t bx[3] = {64, 1, 64}; enc(fn, &P.x, d_in[0], 3, d, s, bx, 128); }
  { cuuint64_t d[3] = {64, 640, 10}, s[2] = {1280, 128}; cuuint32_t bx[3] = {64, 64, 2}; enc(fn, &P.w1a, d_in[4], 3, d, s, bx, 128); }
  { cuuint64_t d[2] = {640, 640}, s[1] = {1280}; cuuint32_t bx[2] = {32, 32}; enc(fn, &P.w1b, d_in[4], 2, d, s, bx, 128); }
  { cuuint64_t d[3] = {320, 1536, 2}, s[2] = {1280, 640}; cuuint32_t bx[3] = {64, 64, 2}; enc(fn, &P.w4a, d_in[7], 3, d, s, bx, 128);
    d[1] = 640; enc(fn, &P.w2a, d_in[5], 3, d, s, bx, 128); }
  { cuuint64_t d[2] = {640, 640}, s[1] = {1280}; cuuint32_t bx[2] = {64, 64}; enc(fn, &P.w2h, d_in[5], 2, d, s, bx, 128); }
  { cuuint64_t d[2] = {640, 1536}, s[1] = {1280}; cuuint32_t bx[2] = {64, 64}; enc(fn, &P.w4h, d_in[7], 2, d, s, bx, 128); }
  { cuuint64_t d[2] = {20544, 32}, s[1] = {41088}; cuuint32_t bx[2] = {168, 32}; enc(fn, &P.wr, d_in[1], 2, d, s, bx, 0); enc(fn, &P.wi, d_in[2], 2, d, s, bx, 0); }
  { cuuint64_t d[4] = {64, 320, 24, 2}, s[3] = {3072, 128, 983040}; cuuint32_t bx[4] = {64, 16, 3, 2}; enc(fn, &P.w3, d_in[6], 4, d, s, bx, 128); }
  { cuuint64_t d[4] = {64, 64, 10, 32}, s[3] = {40960, 128, 1280}; cuuint32_t bx[4] = {64, 32, 1, 1}; enc(fn, &P.t1a, t1, 4, d, s, bx, 128); }
  { cuuint64_t d[4] = {32, 64, 20, 32}, s[3] = {40960, 64, 1280}; cuuint32_t bx[4] = {64, 64, 1, 1}; enc(fn, &P.t1h, t1, 4, d, s, bx, 128); }
  { cuuint64_t d[3] = {64, 2048, 10}, s[2] = {1280, 128}; cuuint32_t bx[3] = {64, 32, 5}; enc(fn, &P.t1l, t1, 3, d, s, bx, 128); }
  { cuuint64_t d[4] = {64, 32, 10, 64}, s[3] = {81920, 128, 1280}; cuuint32_t bx[4] = {64, 32, 5, 1}; enc(fn, &P.t2s, t2, 4, d, s, bx, 128); }
  { cuuint64_t d[2] = {640, 2048}, s[1] = {1280}; cuuint32_t bx[2] = {64, 64}; enc(fn, &P.t2l, t2, 2, d, s, bx, 128); }
  { cuuint64_t d[4] = {320, 64, 2, 32}, s[3] = {40960, 640, 1280}; cuuint32_t ba[4] = {64, 64, 2, 1}, br[4] = {16, 64, 2, 1};
    enc(fn, &P.outa, d_out, 4, d, s, ba, 128); enc(fn, &P.outr, d_out, 4, d, s, br, 32); }

  for (int i = 0; i < 132; i++) {
    const int u = i - 64;
    P.slot[i] = i < 64 ? ((i >> 1) & 7) * 16 + (i >> 4) * 2 + (i & 1) : i < 120 ? (1 + (u >> 1) % 7) * 16 + 8 + (u / 14) * 2 + (u & 1) : i < 124 ? i + 8 : i - 116;
  }
  cudaFuncSetAttribute(fused_kernel, cudaFuncAttributeMaxDynamicSharedMemorySize, SMEM_BYTES);
  fused_kernel<<<132, 512, SMEM_BYTES>>>(P);
}
```

```cpp
#include <cuda_runtime.h>
#include <cuda_bf16.h>
#include <cuda.h>
#include <stdint.h>
#include <stddef.h>

#define DEVI __device__ __forceinline__
#define NPRE_ 3

struct __align__(1024) Scratch {
  unsigned char tab[2 * 409600];
  unsigned char rem[34 * 16384];
  unsigned char h[32 * 20 * 4096];
  unsigned char x1[32 * 20 * 4096];
  unsigned char h2[32 * 48 * 4096];
  unsigned char Y[32 * 10 * 8192];
  __nv_bfloat16 T1[2048 * 640];
  __nv_bfloat16 T2[2048 * 640];
  float2 st1[32 * 8 * 64];
  float cs1[10 * 640];
  float cs3[4 * 1536];
  float4 row[2048];
  unsigned int flag[128 * 32];
  unsigned int epoch[160];
};
static_assert(offsetof(Scratch, x1) == offsetof(Scratch, h) + 2621440 && offsetof(Scratch, h2) == offsetof(Scratch, h) + 5242880, "layout");
__device__ Scratch g_sc;

enum { F_H = 0, F_X1 = 8, F_H2 = 16, F_Y = 48, F_TAB = 80, F_W2 = 81, F_W4 = 82, F_T1 = 83, F_T2 = 85, F_CS3 = 88, F_ST = 96 };

enum : uint32_t {
  NST = 6, SLOT = 28672, NPRE = NPRE_,
  SM = 1024,
  STG = SM + NST * SLOT,
  FB = STG + 24576,
  BAR = FB + 24576,
  ROW = BAR + 384,
  CS1 = ROW + 1024,
  CS3 = CS1 + 640,
  ST1 = CS3 + 768,
  DFR = ST1 + 1024,
  DF0 = STG + 22528,
  CSP = STG, STP = STG + 16384,
  EPO = DFR + 6144,
  PRF = EPO + 16,
  HTB = SM + 204800,
  SMEM_BYTES = PRF + 96 * 4 - SM,
  B_FM = BAR, B_FF = BAR + 48, B_EM = BAR + 96, B_G1 = BAR + 144, B_FFT = BAR + 152, B_ROW = BAR + 160, B_EP = BAR + 168, B_CS = BAR + 176,
  B_WT = BAR + 184,
  B_CSR = BAR + 232,
  B_U = BAR + 240, B_YD = BAR + 248,
  B_H2 = BAR + 256,
  NBAR = 38,
  H128 = 0x40000040u,
  H64 = 0x80000020u,
  SL16 = SLOT >> 4
};
enum { NB_WG2 = 1, NB_INIT = 2, NB_STATS = 3, NB_S = 4, NB_RDY = 5, NB_WG0 = 6, NB_T2 = 8, NB_GO = 10, NB_DMA = 11, NB_F1 = 12, NB_MLP = 13, NB_EP = 14, NB_TAB = 9, NB_FOLD = 15 };
__device__ __forceinline__ int g1_chunk(int b, int it) { const int c = (b >> 2) + (b >> 4) + it; return c >= 10 ? c - 10 : c; }
__host__ __device__ constexpr uint32_t dlo(uint32_t addr, uint32_t lbo) { return (addr >> 4) | ((lbo >> 4) << 16); }

struct Params {
  Scratch* sc;
  const __nv_bfloat16 *px, *pwr, *pwi, *pw1, *pw2, *pw3, *pw4;
  CUtensorMap x, w1a, w1b, wr, wi, w3, t1a, t1h, t1l, t2s, t2l, outa, outr, w2a, w4a, w2h, w4h;
  int slot[132];
};

#define SPIN_MAX 4000000
#define G0M 0
#define G5C(j) ((0x26510 >> (4 * (j))) & 15)
#define FLAGA 5
#define T1GAP 500
#define T1FREE 2
DEVI void mbar_init(uint32_t b, int c) { asm volatile("mbarrier.init.shared::cta.b64 [%0], %1;" ::"r"(b), "r"(c)); }
DEVI void mbar_expect(uint32_t b, int bytes) { asm volatile("mbarrier.arrive.expect_tx.shared::cta.b64 _, [%0], %1;" ::"r"(b), "r"(bytes) : "memory"); }
DEVI void mbar_arrive(uint32_t b) { asm volatile("mbarrier.arrive.shared::cta.b64 _, [%0];" ::"r"(b) : "memory"); }
DEVI void mbar_arrive_n(uint32_t b, uint32_t n) { asm volatile("mbarrier.arrive.shared::cta.b64 _, [%0], %1;" ::"r"(b), "r"(n) : "memory"); }
DEVI void mbar_wait(uint32_t b, uint32_t par) {
  asm volatile("{\n.reg .pred p;\nL_%=:\nmbarrier.try_wait.parity.shared::cta.b64 p, [%0], %1;\n@!p bra.uni L_%=;\n}" ::"r"(b), "r"(par) : "memory");
}
DEVI bool elect() { uint32_t p; asm volatile("{\n.reg .pred P;\nelect.sync _|P, 0xffffffff;\nselp.u32 %0,1,0,P;\n}" : "=r"(p)); return p; }
DEVI void nb_sync(int id, int n) { asm volatile("bar.sync %0, %1;" ::"r"(id), "r"(n) : "memory"); }
DEVI void nb_arrive(int id, int n) { asm volatile("bar.arrive %0, %1;" ::"r"(id), "r"(n) : "memory"); }
DEVI void fence_async_smem() { asm volatile("fence.proxy.async.shared::cta;" ::: "memory"); }
DEVI void fence_async_gmem() { asm volatile("fence.proxy.async.global;" ::: "memory"); }
DEVI void bulk_ld(uint32_t dst, const void* src, int bytes, uint32_t bar) {
  asm volatile("cp.async.bulk.shared::cluster.global.mbarrier::complete_tx::bytes [%0], [%1], %2, [%3];" ::"r"(dst), "l"(src), "r"(bytes), "r"(bar) : "memory");
}
DEVI void bulk_st(void* dst, uint32_t src, int bytes) {
  asm volatile("cp.async.bulk.global.shared::cta.bulk_group [%0], [%1], %2;" ::"l"(dst), "r"(src), "r"(bytes) : "memory");
}
DEVI void tma_ld2(uint32_t dst, const CUtensorMap* m, uint32_t bar, int c0, int c1) {
  asm volatile("cp.async.bulk.tensor.2d.shared::cluster.global.mbarrier::complete_tx::bytes [%0], [%1, {%3, %4}], [%2];" ::"r"(dst), "l"(m), "r"(bar), "r"(c0), "r"(c1) : "memory");
}
DEVI void tma_ld3(uint32_t dst, const CUtensorMap* m, uint32_t bar, int c0, int c1, int c2) {
  asm volatile("cp.async.bulk.tensor.3d.shared::cluster.global.mbarrier::complete_tx::bytes [%0], [%1, {%3, %4, %5}], [%2];" ::"r"(dst), "l"(m), "r"(bar), "r"(c0), "r"(c1), "r"(c2) : "memory");
}
DEVI void tma_ld4(uint32_t dst, const CUtensorMap* m, uint32_t bar, int c0, int c1, int c2, int c3) {
  asm volatile("cp.async.bulk.tensor.4d.shared::cluster.global.mbarrier::complete_tx::bytes [%0], [%1, {%3, %4, %5, %6}], [%2];" ::"r"(dst), "l"(m), "r"(bar), "r"(c0), "r"(c1), "r"(c2), "r"(c3) : "memory");
}
DEVI void tma_st4(const CUtensorMap* m, uint32_t src, int c0, int c1, int c2, int c3) {
  asm volatile("cp.async.bulk.tensor.4d.global.shared::cta.bulk_group [%0, {%2, %3, %4, %5}], [%1];" ::"l"(m), "r"(src), "r"(c0), "r"(c1), "r"(c2), "r"(c3) : "memory");
}
DEVI void tmap_pf(const CUtensorMap* m) { asm volatile("prefetch.tensormap [%0];" ::"l"(m) : "memory"); }
DEVI void bulk_commit() { asm volatile("cp.async.bulk.commit_group;" ::: "memory"); }
DEVI void bulk_wait_read() { asm volatile("cp.async.bulk.wait_group.read 0;" ::: "memory"); }
DEVI void bulk_wait_all() { asm volatile("cp.async.bulk.wait_group 0;" ::: "memory"); }
#define SC(member, off) ((unsigned char*)P.sc + (uint32_t)(offsetof(Scratch, member) + (off)))
DEVI unsigned char* keep(unsigned char* p) { asm volatile("" : "+l"(p)); return p; }
DEVI unsigned char* flag_ptr(Scratch* sc, uint32_t f) { return (unsigned char*)sc + (uint32_t)(offsetof(Scratch, flag) + f * 128); }
DEVI void flag_add(Scratch* sc, uint32_t f) { asm volatile("red.relaxed.gpu.global.add.u32 [%0], 1;" ::"l"(flag_ptr(sc, f)) : "memory"); }
DEVI void flag_wait(Scratch* sc, uint32_t f, uint32_t target) {
  asm volatile("{\n.reg .pred p;\n.reg .u32 c, v;\nmov.u32 c, 0;\nL_%=:\nld.relaxed.gpu.global.u32 v, [%0];\nsub.u32 v, v, %1;\n"
               "setp.ge.s32 p, v, 0;\n@p bra.uni D_%=;\nadd.u32 c, c, 1;\nsetp.lt.u32 p, c, 4000000;\n@p bra.uni L_%=;\ntrap;\nD_%=:\n"
               "fence.proxy.async.global;\n}" ::"l"(flag_ptr(sc, f)), "r"(target) : "memory");
}
DEVI void watch(Scratch* sc, uint32_t f, uint32_t target, int k) { flag_wait(sc, f, target); if (elect()) mbar_arrive(B_WT + k * 8); __syncwarp(); }
DEVI void watched(int k) { mbar_wait(B_WT + k * 8, 0); fence_async_gmem(); }
DEVI void wg_fence() { asm volatile("wgmma.fence.sync.aligned;" ::: "memory"); }
DEVI void wg_commit() { asm volatile("wgmma.commit_group.sync.aligned;" ::: "memory"); }
template <int N> DEVI void wg_wait() { asm volatile("wgmma.wait_group.sync.aligned %0;" ::"n"(N) : "memory"); }
DEVI void stsm4(uint32_t a, uint32_t r0, uint32_t r1, uint32_t r2, uint32_t r3) {
  asm volatile("stmatrix.sync.aligned.m8n8.x4.shared.b16 [%0], {%1,%2,%3,%4};" ::"r"(a), "r"(r0), "r"(r1), "r"(r2), "r"(r3) : "memory");
}
DEVI void ldsm4(uint32_t a, uint32_t& r0, uint32_t& r1, uint32_t& r2, uint32_t& r3) {
  asm volatile("ldmatrix.sync.aligned.m8n8.x4.shared.b16 {%0,%1,%2,%3}, [%4];" : "=r"(r0), "=r"(r1), "=r"(r2), "=r"(r3) : "r"(a) : "memory");
}
DEVI uint32_t pack2(float lo, float hi) { uint32_t r; asm("cvt.rn.bf16x2.f32 %0, %1, %2;" : "=r"(r) : "f"(hi), "f"(lo)); return r; }
DEVI float bf_lo(uint32_t v) { return __uint_as_float(v << 16); }
DEVI float bf_hi(uint32_t v) { return __uint_as_float(v & 0xffff0000u); }
DEVI float2 lds_f2(uint32_t a) { float2 v; asm volatile("ld.shared.v2.f32 {%0,%1}, [%2];" : "=f"(v.x), "=f"(v.y) : "r"(a)); return v; }
DEVI float4 lds_f4(uint32_t a) { float4 v; asm volatile("ld.shared.v4.f32 {%0,%1,%2,%3}, [%4];" : "=f"(v.x), "=f"(v.y), "=f"(v.z), "=f"(v.w) : "r"(a)); return v; }
DEVI uint4 lds_u4(uint32_t a) { uint4 v; asm volatile("ld.shared.v4.u32 {%0,%1,%2,%3}, [%4];" : "=r"(v.x), "=r"(v.y), "=r"(v.z), "=r"(v.w) : "r"(a)); return v; }
DEVI uint32_t lds_u32(uint32_t a) { uint32_t v; asm volatile("ld.shared.u32 %0, [%1];" : "=r"(v) : "r"(a)); return v; }
DEVI void sts_u32(uint32_t a, uint32_t v) { asm volatile("st.shared.u32 [%0], %1;" ::"r"(a), "r"(v) : "memory"); }
DEVI void sts_f2(uint32_t a, float x, float y) { asm volatile("st.shared.v2.f32 [%0], {%1,%2};" ::"r"(a), "f"(x), "f"(y) : "memory"); }
DEVI void sts_f4(uint32_t a, float x, float y, float z, float w) { asm volatile("st.shared.v4.f32 [%0], {%1,%2,%3,%4};" ::"r"(a), "f"(x), "f"(y), "f"(z), "f"(w) : "memory"); }
DEVI void sts_u4(uint32_t a, uint32_t x, uint32_t y, uint32_t z, uint32_t w) { asm volatile("st.shared.v4.u32 [%0], {%1,%2,%3,%4};" ::"r"(a), "r"(x), "r"(y), "r"(z), "r"(w) : "memory"); }
DEVI uint32_t ldg_u32(const void* p) { uint32_t v; asm volatile("ld.global.u32 %0, [%1];" : "=r"(v) : "l"(p)); return v; }
DEVI uint32_t ldg_nc_u32(const void* p) { uint32_t v; asm volatile("ld.global.nc.u32 %0, [%1];" : "=r"(v) : "l"(p)); return v; }
DEVI uint32_t ldg_nc_u16(const void* p) { uint32_t v; asm volatile("ld.global.nc.u16 %0, [%1];" : "=r"(v) : "l"(p)); return v; }
DEVI uint4 ldg_nc_u4(const void* p) { uint4 v; asm volatile("ld.global.nc.v4.u32 {%0,%1,%2,%3}, [%4];" : "=r"(v.x), "=r"(v.y), "=r"(v.z), "=r"(v.w) : "l"(p)); return v; }
DEVI uint2 ldg_nc_u2(const void* p) { uint2 v; asm volatile("ld.global.nc.v2.u32 {%0,%1}, [%2];" : "=r"(v.x), "=r"(v.y) : "l"(p)); return v; }
DEVI float2 ldg_cg_f2(const void* p) { float2 v; asm volatile("ld.global.cg.v2.f32 {%0,%1}, [%2];" : "=f"(v.x), "=f"(v.y) : "l"(p)); return v; }
DEVI float tanh_fast(float x) { float y; asm("tanh.approx.f32 %0, %1;" : "=f"(y) : "f"(x)); return y; }
DEVI float silu(float v) { float hv = 0.5f * v; return fmaf(hv, tanh_fast(hv), hv); }

template <int N> DEVI void zero(float (&a)[N]) {
#pragma unroll
  for (int i = 0; i < N; i++) a[i] = 0.f;
}
template <int N> DEVI void pin(float (&a)[N]) {
#pragma unroll
  for (int i = 0; i < N; i++) asm volatile("" : "+f"(a[i])::"memory");
}
DEVI void pin1(uint32_t& v) { asm volatile("" : "+r"(v)::"memory"); }
DEVI uint32_t hadd2(uint32_t a, uint32_t b) { uint32_t r; asm("add.rn.bf16x2 %0, %1, %2;" : "=r"(r) : "r"(a), "r"(b)); return r; }
DEVI uint32_t hfma2(uint32_t a, uint32_t b, uint32_t c) { uint32_t r; asm("fma.rn.bf16x2 %0, %1, %2, %3;" : "=r"(r) : "r"(a), "r"(b), "r"(c)); return r; }
DEVI void landed(uint32_t v) { asm volatile("{\n.reg .pred p;\nsetp.eq.u32 p, %0, 0x7fc17fc1;\n@p st.shared.u32 [%1], %0;\n}" ::"r"(v), "r"(EPO + 8) : "memory"); }
DEVI void staged(uint32_t bar, int lane) { fence_async_smem(); __syncwarp(); if (lane == 0) mbar_arrive(bar); }
DEVI float rsq(float x) { float y; asm("rsqrt.approx.ftz.f32 %0, %1;" : "=f"(y) : "f"(x)); return y; }
DEVI void acc8(float (&c)[8], const uint4& v) {
  c[0] += bf_lo(v.x); c[1] += bf_hi(v.x); c[2] += bf_lo(v.y); c[3] += bf_hi(v.y);
  c[4] += bf_lo(v.z); c[5] += bf_hi(v.z); c[6] += bf_lo(v.w); c[7] += bf_hi(v.w);
}
template<int TB,uint32_t HA,uint32_t HB> DEVI void wg_ss_80(float (&d)[40], uint32_t a, uint32_t b, int sd){
  asm volatile("{\n.reg .b64 da, db;\n.reg .pred p;\nsetp.ne.b32 p, %45, 0;\nmov.b64 da, {%40, %42};\nmov.b64 db, {%41, %43};\nwgmma.mma_async.sync.aligned.m64n80k16.f32.bf16.bf16 {%0,%1,%2,%3,%4,%5,%6,%7,%8,%9,%10,%11,%12,%13,%14,%15,%16,%17,%18,%19,%20,%21,%22,%23,%24,%25,%26,%27,%28,%29,%30,%31,%32,%33,%34,%35,%36,%37,%38,%39}, da, db, p, 1, 1, 0, %44;\n}\n"
    : "+f"(d[0]),"+f"(d[1]),"+f"(d[2]),"+f"(d[3]),"+f"(d[4]),"+f"(d[5]),"+f"(d[6]),"+f"(d[7]),"+f"(d[8]),"+f"(d[9]),"+f"(d[10]),"+f"(d[11]),"+f"(d[12]),"+f"(d[13]),"+f"(d[14]),"+f"(d[15]),"+f"(d[16]),"+f"(d[17]),"+f"(d[18]),"+f"(d[19]),"+f"(d[20]),"+f"(d[21]),"+f"(d[22]),"+f"(d[23]),"+f"(d[24]),"+f"(d[25]),"+f"(d[26]),"+f"(d[27]),"+f"(d[28]),"+f"(d[29]),"+f"(d[30]),"+f"(d[31]),"+f"(d[32]),"+f"(d[33]),"+f"(d[34]),"+f"(d[35]),"+f"(d[36]),"+f"(d[37]),"+f"(d[38]),"+f"(d[39])
    : "r"(a), "r"(b), "n"(HA), "n"(HB), "n"(TB), "r"(sd));
}
template<int TB,uint32_t HA,uint32_t HB> DEVI void wg_ss_160(float (&d)[80], uint32_t a, uint32_t b, int sd){
  asm volatile("{\n.reg .b64 da, db;\n.reg .pred p;\nsetp.ne.b32 p, %85, 0;\nmov.b64 da, {%80, %82};\nmov.b64 db, {%81, %83};\nwgmma.mma_async.sync.aligned.m64n160k16.f32.bf16.bf16 {%0,%1,%2,%3,%4,%5,%6,%7,%8,%9,%10,%11,%12,%13,%14,%15,%16,%17,%18,%19,%20,%21,%22,%23,%24,%25,%26,%27,%28,%29,%30,%31,%32,%33,%34,%35,%36,%37,%38,%39,%40,%41,%42,%43,%44,%45,%46,%47,%48,%49,%50,%51,%52,%53,%54,%55,%56,%57,%58,%59,%60,%61,%62,%63,%64,%65,%66,%67,%68,%69,%70,%71,%72,%73,%74,%75,%76,%77,%78,%79}, da, db, p, 1, 1, 0, %84;\n}\n"
    : "+f"(d[0]),"+f"(d[1]),"+f"(d[2]),"+f"(d[3]),"+f"(d[4]),"+f"(d[5]),"+f"(d[6]),"+f"(d[7]),"+f"(d[8]),"+f"(d[9]),"+f"(d[10]),"+f"(d[11]),"+f"(d[12]),"+f"(d[13]),"+f"(d[14]),"+f"(d[15]),"+f"(d[16]),"+f"(d[17]),"+f"(d[18]),"+f"(d[19]),"+f"(d[20]),"+f"(d[21]),"+f"(d[22]),"+f"(d[23]),"+f"(d[24]),"+f"(d[25]),"+f"(d[26]),"+f"(d[27]),"+f"(d[28]),"+f"(d[29]),"+f"(d[30]),"+f"(d[31]),"+f"(d[32]),"+f"(d[33]),"+f"(d[34]),"+f"(d[35]),"+f"(d[36]),"+f"(d[37]),"+f"(d[38]),"+f"(d[39]),"+f"(d[40]),"+f"(d[41]),"+f"(d[42]),"+f"(d[43]),"+f"(d[44]),"+f"(d[45]),"+f"(d[46]),"+f"(d[47]),"+f"(d[48]),"+f"(d[49]),"+f"(d[50]),"+f"(d[51]),"+f"(d[52]),"+f"(d[53]),"+f"(d[54]),"+f"(d[55]),"+f"(d[56]),"+f"(d[57]),"+f"(d[58]),"+f"(d[59]),"+f"(d[60]),"+f"(d[61]),"+f"(d[62]),"+f"(d[63]),"+f"(d[64]),"+f"(d[65]),"+f"(d[66]),"+f"(d[67]),"+f"(d[68]),"+f"(d[69]),"+f"(d[70]),"+f"(d[71]),"+f"(d[72]),"+f"(d[73]),"+f"(d[74]),"+f"(d[75]),"+f"(d[76]),"+f"(d[77]),"+f"(d[78]),"+f"(d[79])
    : "r"(a), "r"(b), "n"(HA), "n"(HB), "n"(TB), "r"(sd));
}
template<int TB,uint32_t HA,uint32_t HB> DEVI void wg_ss_192(float (&d)[96], uint32_t a, uint32_t b, int sd){
  asm volatile("{\n.reg .b64 da, db;\n.reg .pred p;\nsetp.ne.b32 p, %101, 0;\nmov.b64 da, {%96, %98};\nmov.b64 db, {%97, %99};\nwgmma.mma_async.sync.aligned.m64n192k16.f32.bf16.bf16 {%0,%1,%2,%3,%4,%5,%6,%7,%8,%9,%10,%11,%12,%13,%14,%15,%16,%17,%18,%19,%20,%21,%22,%23,%24,%25,%26,%27,%28,%29,%30,%31,%32,%33,%34,%35,%36,%37,%38,%39,%40,%41,%42,%43,%44,%45,%46,%47,%48,%49,%50,%51,%52,%53,%54,%55,%56,%57,%58,%59,%60,%61,%62,%63,%64,%65,%66,%67,%68,%69,%70,%71,%72,%73,%74,%75,%76,%77,%78,%79,%80,%81,%82,%83,%84,%85,%86,%87,%88,%89,%90,%91,%92,%93,%94,%95}, da, db, p, 1, 1, 0, %100;\n}\n"
    : "+f"(d[0]),"+f"(d[1]),"+f"(d[2]),"+f"(d[3]),"+f"(d[4]),"+f"(d[5]),"+f"(d[6]),"+f"(d[7]),"+f"(d[8]),"+f"(d[9]),"+f"(d[10]),"+f"(d[11]),"+f"(d[12]),"+f"(d[13]),"+f"(d[14]),"+f"(d[15]),"+f"(d[16]),"+f"(d[17]),"+f"(d[18]),"+f"(d[19]),"+f"(d[20]),"+f"(d[21]),"+f"(d[22]),"+f"(d[23]),"+f"(d[24]),"+f"(d[25]),"+f"(d[26]),"+f"(d[27]),"+f"(d[28]),"+f"(d[29]),"+f"(d[30]),"+f"(d[31]),"+f"(d[32]),"+f"(d[33]),"+f"(d[34]),"+f"(d[35]),"+f"(d[36]),"+f"(d[37]),"+f"(d[38]),"+f"(d[39]),"+f"(d[40]),"+f"(d[41]),"+f"(d[42]),"+f"(d[43]),"+f"(d[44]),"+f"(d[45]),"+f"(d[46]),"+f"(d[47]),"+f"(d[48]),"+f"(d[49]),"+f"(d[50]),"+f"(d[51]),"+f"(d[52]),"+f"(d[53]),"+f"(d[54]),"+f"(d[55]),"+f"(d[56]),"+f"(d[57]),"+f"(d[58]),"+f"(d[59]),"+f"(d[60]),"+f"(d[61]),"+f"(d[62]),"+f"(d[63]),"+f"(d[64]),"+f"(d[65]),"+f"(d[66]),"+f"(d[67]),"+f"(d[68]),"+f"(d[69]),"+f"(d[70]),"+f"(d[71]),"+f"(d[72]),"+f"(d[73]),"+f"(d[74]),"+f"(d[75]),"+f"(d[76]),"+f"(d[77]),"+f"(d[78]),"+f"(d[79]),"+f"(d[80]),"+f"(d[81]),"+f"(d[82]),"+f"(d[83]),"+f"(d[84]),"+f"(d[85]),"+f"(d[86]),"+f"(d[87]),"+f"(d[88]),"+f"(d[89]),"+f"(d[90]),"+f"(d[91]),"+f"(d[92]),"+f"(d[93]),"+f"(d[94]),"+f"(d[95])
    : "r"(a), "r"(b), "n"(HA), "n"(HB), "n"(TB), "r"(sd));
}
template<int SD,int TB,uint32_t HB> DEVI void wg_rs_32(float (&d)[16], uint32_t a0, uint32_t a1, uint32_t a2, uint32_t a3, uint32_t b){
  asm volatile("{\n.reg .b64 db;\nmov.b64 db, {%20, %21};\nwgmma.mma_async.sync.aligned.m64n32k16.f32.bf16.bf16 {%0,%1,%2,%3,%4,%5,%6,%7,%8,%9,%10,%11,%12,%13,%14,%15}, {%16,%17,%18,%19}, db, %22, 1, 1, %23;\n}\n"
    : "+f"(d[0]),"+f"(d[1]),"+f"(d[2]),"+f"(d[3]),"+f"(d[4]),"+f"(d[5]),"+f"(d[6]),"+f"(d[7]),"+f"(d[8]),"+f"(d[9]),"+f"(d[10]),"+f"(d[11]),"+f"(d[12]),"+f"(d[13]),"+f"(d[14]),"+f"(d[15])
    : "r"(a0),"r"(a1),"r"(a2),"r"(a3), "r"(b), "n"(HB), "n"(SD), "n"(TB));
}
template<int SD,int TB,uint32_t HB> DEVI void wg_rs_64(float (&d)[32], uint32_t a0, uint32_t a1, uint32_t a2, uint32_t a3, uint32_t b){
  asm volatile("{\n.reg .b64 db;\nmov.b64 db, {%36, %37};\nwgmma.mma_async.sync.aligned.m64n64k16.f32.bf16.bf16 {%0,%1,%2,%3,%4,%5,%6,%7,%8,%9,%10,%11,%12,%13,%14,%15,%16,%17,%18,%19,%20,%21,%22,%23,%24,%25,%26,%27,%28,%29,%30,%31}, {%32,%33,%34,%35}, db, %38, 1, 1, %39;\n}\n"
    : "+f"(d[0]),"+f"(d[1]),"+f"(d[2]),"+f"(d[3]),"+f"(d[4]),"+f"(d[5]),"+f"(d[6]),"+f"(d[7]),"+f"(d[8]),"+f"(d[9]),"+f"(d[10]),"+f"(d[11]),"+f"(d[12]),"+f"(d[13]),"+f"(d[14]),"+f"(d[15]),"+f"(d[16]),"+f"(d[17]),"+f"(d[18]),"+f"(d[19]),"+f"(d[20]),"+f"(d[21]),"+f"(d[22]),"+f"(d[23]),"+f"(d[24]),"+f"(d[25]),"+f"(d[26]),"+f"(d[27]),"+f"(d[28]),"+f"(d[29]),"+f"(d[30]),"+f"(d[31])
    : "r"(a0),"r"(a1),"r"(a2),"r"(a3), "r"(b), "n"(HB), "n"(SD), "n"(TB));
}
template<int SD,int TB,uint32_t HB> DEVI void wg_rs_128(float (&d)[64], uint32_t a0, uint32_t a1, uint32_t a2, uint32_t a3, uint32_t b){
  asm volatile("{\n.reg .b64 db;\nmov.b64 db, {%68, %69};\nwgmma.mma_async.sync.aligned.m64n128k16.f32.bf16.bf16 {%0,%1,%2,%3,%4,%5,%6,%7,%8,%9,%10,%11,%12,%13,%14,%15,%16,%17,%18,%19,%20,%21,%22,%23,%24,%25,%26,%27,%28,%29,%30,%31,%32,%33,%34,%35,%36,%37,%38,%39,%40,%41,%42,%43,%44,%45,%46,%47,%48,%49,%50,%51,%52,%53,%54,%55,%56,%57,%58,%59,%60,%61,%62,%63}, {%64,%65,%66,%67}, db, %70, 1, 1, %71;\n}\n"
    : "+f"(d[0]),"+f"(d[1]),"+f"(d[2]),"+f"(d[3]),"+f"(d[4]),"+f"(d[5]),"+f"(d[6]),"+f"(d[7]),"+f"(d[8]),"+f"(d[9]),"+f"(d[10]),"+f"(d[11]),"+f"(d[12]),"+f"(d[13]),"+f"(d[14]),"+f"(d[15]),"+f"(d[16]),"+f"(d[17]),"+f"(d[18]),"+f"(d[19]),"+f"(d[20]),"+f"(d[21]),"+f"(d[22]),"+f"(d[23]),"+f"(d[24]),"+f"(d[25]),"+f"(d[26]),"+f"(d[27]),"+f"(d[28]),"+f"(d[29]),"+f"(d[30]),"+f"(d[31]),"+f"(d[32]),"+f"(d[33]),"+f"(d[34]),"+f"(d[35]),"+f"(d[36]),"+f"(d[37]),"+f"(d[38]),"+f"(d[39]),"+f"(d[40]),"+f"(d[41]),"+f"(d[42]),"+f"(d[43]),"+f"(d[44]),"+f"(d[45]),"+f"(d[46]),"+f"(d[47]),"+f"(d[48]),"+f"(d[49]),"+f"(d[50]),"+f"(d[51]),"+f"(d[52]),"+f"(d[53]),"+f"(d[54]),"+f"(d[55]),"+f"(d[56]),"+f"(d[57]),"+f"(d[58]),"+f"(d[59]),"+f"(d[60]),"+f"(d[61]),"+f"(d[62]),"+f"(d[63])
    : "r"(a0),"r"(a1),"r"(a2),"r"(a3), "r"(b), "n"(HB), "n"(SD), "n"(TB));
}
template<int SD,int TB,uint32_t HB> DEVI void wg_rs_160(float (&d)[80], uint32_t a0, uint32_t a1, uint32_t a2, uint32_t a3, uint32_t b){
  asm volatile("{\n.reg .b64 db;\nmov.b64 db, {%84, %85};\nwgmma.mma_async.sync.aligned.m64n160k16.f32.bf16.bf16 {%0,%1,%2,%3,%4,%5,%6,%7,%8,%9,%10,%11,%12,%13,%14,%15,%16,%17,%18,%19,%20,%21,%22,%23,%24,%25,%26,%27,%28,%29,%30,%31,%32,%33,%34,%35,%36,%37,%38,%39,%40,%41,%42,%43,%44,%45,%46,%47,%48,%49,%50,%51,%52,%53,%54,%55,%56,%57,%58,%59,%60,%61,%62,%63,%64,%65,%66,%67,%68,%69,%70,%71,%72,%73,%74,%75,%76,%77,%78,%79}, {%80,%81,%82,%83}, db, %86, 1, 1, %87;\n}\n"
    : "+f"(d[0]),"+f"(d[1]),"+f"(d[2]),"+f"(d[3]),"+f"(d[4]),"+f"(d[5]),"+f"(d[6]),"+f"(d[7]),"+f"(d[8]),"+f"(d[9]),"+f"(d[10]),"+f"(d[11]),"+f"(d[12]),"+f"(d[13]),"+f"(d[14]),"+f"(d[15]),"+f"(d[16]),"+f"(d[17]),"+f"(d[18]),"+f"(d[19]),"+f"(d[20]),"+f"(d[21]),"+f"(d[22]),"+f"(d[23]),"+f"(d[24]),"+f"(d[25]),"+f"(d[26]),"+f"(d[27]),"+f"(d[28]),"+f"(d[29]),"+f"(d[30]),"+f"(d[31]),"+f"(d[32]),"+f"(d[33]),"+f"(d[34]),"+f"(d[35]),"+f"(d[36]),"+f"(d[37]),"+f"(d[38]),"+f"(d[39]),"+f"(d[40]),"+f"(d[41]),"+f"(d[42]),"+f"(d[43]),"+f"(d[44]),"+f"(d[45]),"+f"(d[46]),"+f"(d[47]),"+f"(d[48]),"+f"(d[49]),"+f"(d[50]),"+f"(d[51]),"+f"(d[52]),"+f"(d[53]),"+f"(d[54]),"+f"(d[55]),"+f"(d[56]),"+f"(d[57]),"+f"(d[58]),"+f"(d[59]),"+f"(d[60]),"+f"(d[61]),"+f"(d[62]),"+f"(d[63]),"+f"(d[64]),"+f"(d[65]),"+f"(d[66]),"+f"(d[67]),"+f"(d[68]),"+f"(d[69]),"+f"(d[70]),"+f"(d[71]),"+f"(d[72]),"+f"(d[73]),"+f"(d[74]),"+f"(d[75]),"+f"(d[76]),"+f"(d[77]),"+f"(d[78]),"+f"(d[79])
    : "r"(a0),"r"(a1),"r"(a2),"r"(a3), "r"(b), "n"(HB), "n"(SD), "n"(TB));
}

#define STAMP(i)
#define STAMPW(i)
#define GSTAMP(i)

DEVI uint32_t sw64(uint32_t row, uint32_t c) { return row * 64 + ((c ^ ((row >> 1) & 3)) << 4); }
DEVI uint32_t sw128(uint32_t row, uint32_t c) { return row * 128 + ((c ^ (row & 7)) << 4); }

DEVI float gelu_s(float t, float k0, float k1, float hr) {
  const float h = t * hr;
  return fmaf(h, tanh_fast(t * fmaf(t * t, k1, k0)), h);
}
struct GeluK { float mu0, mu1, a0, a1, ah, b0, b1, bh; };
DEVI GeluK gelu_k(float mu0, float mu1, float rs0, float rs1) {
  return GeluK{mu0, mu1, 0.7978845608f * rs0, 0.0356774081f * rs0 * rs0 * rs0, 0.5f * rs0, 0.7978845608f * rs1, 0.0356774081f * rs1 * rs1 * rs1, 0.5f * rs1};
}
DEVI void gelu_unit(const float* a, const GeluK& k, float2 c, float2 d, uint32_t dst) {
  stsm4(dst, pack2(gelu_s(fmaf(-k.mu0, c.x, a[0]), k.a0, k.a1, k.ah), gelu_s(fmaf(-k.mu0, c.y, a[1]), k.a0, k.a1, k.ah)),
        pack2(gelu_s(fmaf(-k.mu1, c.x, a[2]), k.b0, k.b1, k.bh), gelu_s(fmaf(-k.mu1, c.y, a[3]), k.b0, k.b1, k.bh)),
        pack2(gelu_s(fmaf(-k.mu0, d.x, a[4]), k.a0, k.a1, k.ah), gelu_s(fmaf(-k.mu0, d.y, a[5]), k.a0, k.a1, k.ah)),
        pack2(gelu_s(fmaf(-k.mu1, d.x, a[6]), k.b0, k.b1, k.bh), gelu_s(fmaf(-k.mu1, d.y, a[7]), k.b0, k.b1, k.bh)));
}

DEVI void d_frags(uint32_t (&D)[8], int c0, int cs, int lane) {
#pragma unroll
  for (int i = 0; i < 4; i++) {
    const int v = c0 + cs * (8 * i + 2 * (lane & 3)) + 1024;
    const float a0 = (float)((v & 2047) - 1024) * 0.0030679615757712823f, a1 = (float)(((v + cs) & 2047) - 1024) * 0.0030679615757712823f;
    D[2 * i] = pack2(__cosf(a0), __cosf(a1)); D[2 * i + 1] = pack2(__sinf(a0), __sinf(a1));
  }
}

DEVI void fold(int b, int j, uint32_t row128, uint32_t sx, float mu0, float mu1, int odd) {
  const uint32_t dst = SM + (j ? j - 1 : 5) * SLOT + row128;
  const uint32_t oth = (j < 2 ? SM + 4 * SLOT + 8192 + j * 8192 : j == 2 ? FB + 16384 : j == 3 ? FB : SM + 4 * SLOT) + row128;
  const bool lo = g1_chunk(b, j) < 5;
  const uint32_t xa = lo ? oth : dst, xb = lo ? dst : oth;
  const float km = odd ? 0.f : -2.f;
  const uint32_t np0 = pack2(mu0 * km, mu0 * km), np1 = pack2(mu1 * km, mu1 * km), sg = odd ? 0xbf80bf80u : 0x3f803f80u;
  uint32_t u[16], v[16];
#pragma unroll
  for (int kk = 0; kk < 4; kk++) {
    ldsm4(xa + (sx ^ (kk << 5)), u[4 * kk], u[4 * kk + 1], u[4 * kk + 2], u[4 * kk + 3]);
    ldsm4(xb + (sx ^ (kk << 5)), v[4 * kk], v[4 * kk + 1], v[4 * kk + 2], v[4 * kk + 3]);
  }
#pragma unroll
  for (int kk = 0; kk < 4; kk++)
    stsm4(dst + (sx ^ (kk << 5)), hfma2(v[4 * kk], sg, hadd2(u[4 * kk], np0)), hfma2(v[4 * kk + 1], sg, hadd2(u[4 * kk + 1], np1)),
          hfma2(v[4 * kk + 2], sg, hadd2(u[4 * kk + 2], np0)), hfma2(v[4 * kk + 3], sg, hadd2(u[4 * kk + 3], np1)));
}

DEVI void mlp_role(const Params& P, int b, int q, int wg, int w, uint32_t t_start) {
  const int tid = threadIdx.x, lane = tid & 31;
  const int odd = q & 1;
  const int r0 = 16 * w + (lane >> 2);
  const int srow = 16 * w + (lane & 7) + ((lane >> 3) & 1) * 8;
  const int schk = lane >> 4;
  uint32_t phM = 0;
  uint32_t s = 0, sp = 0;
  const bool rel = (tid & 127) == 0;
#define STAGE_WAIT() mbar_wait(B_FM + s * 8, (phM >> s) & 1); phM ^= 1u << s; const uint32_t so = s * SL16; wg_fence();
#define STAGE_NEXT() wg_commit(); wg_wait<1>(); if (rel && it > 0) mbar_arrive(B_EM + sp * 8); sp = s; s = s == NST - 1 ? 0 : s + 1;
#define STAGE_END() wg_wait<0>(); if (rel) mbar_arrive(B_EM + sp * 8);

  const int ga = 2 * wg + odd, gs = odd ? 0 : 4;
  const uint32_t oA = sw64(srow, schk), oB = sw64(srow, 2 + schk);
  constexpr uint32_t dA = dlo(SM, 16);
  const uint32_t dBlo = dlo(SM + 8192, 16384) + wg * (dlo(8192, 0) - dlo(0, 8192 - 32));
  const uint32_t dBhi = dBlo + dlo(4096, 0) - dlo(0, 4096 - 64);
  float mu0, mu1;
  const uint32_t o128 = srow * 128, x128 = ((srow & 7) ^ schk) << 4;
  uint32_t wf[20], nr = 0, ni = 0;
  const int k1 = 2 * b + (q >> 1), k2 = 8 * w + (lane >> 2);
  const bool nyq = !odd && !wg && (lane & 3) == 0;
  uint32_t xf[20], yv[20];
#pragma unroll
  for (int i = 0; i < 20; i++) xf[i] = 0;
  {
    float acc[40];
    const uint32_t dB1 = dBlo + dlo(4096, FB - SM - 28672);
    STAMPW(80);
#pragma unroll 1
    for (int it = 0; it < 10; it++) {
      mbar_wait(B_FM + s * 8, (phM >> s) & 1); phM ^= 1u << s;
      const uint32_t so = s * SL16;
      if (it == 0) STAMPW(82);
      const int ck = g1_chunk(b, it);
      if (ck == q + 5 * wg) {
#pragma unroll
        for (int j = 0; j < 4; j++) ldsm4(SM + s * SLOT + o128 + (x128 ^ (j << 5)), xf[4 * j], xf[4 * j + 1], xf[4 * j + 2], xf[4 * j + 3]);
      }
      if (ck == 4 + 5 * wg) { ldsm4(SM + s * SLOT + o128 + (x128 ^ (q << 5)), xf[16], xf[17], xf[18], xf[19]); }
      const uint32_t dh = dB1 + so - s * dlo(0, SLOT - 4096);
      wg_fence();
#pragma unroll
      for (int kk = 0; kk < 4; kk++) wg_ss_80<1, H128, H128>(acc, dA + so + kk * 2, (kk < 2 ? dBlo + so : dh) + (kk & 1) * 128, kk ? 1 : it);
      STAGE_NEXT();
      landed(xf[0] ^ xf[4] ^ xf[8] ^ xf[12] ^ xf[16]);
    }
    wg_fence();
    STAGE_END();
    STAMPW(12); GSTAMP(16);
    const int carry = (b + (q & 2 ? 2 : 1) * (odd ? -1 : 1)) >> 5;
    const int drow = (srow + carry) & 63;
    const uint32_t dA_ = STG + sw64(drow, schk), dB_ = STG + sw64(drow, 2 + schk);
    nb_sync(NB_STATS, 416);
    const float4 s0 = lds_f4(ROW + r0 * 16), s1 = lds_f4(ROW + 128 + r0 * 16);
    mu0 = s0.x; mu1 = s1.x;
    const float rs0 = (r0 + carry < 0) ? 0.f : s0.z, rs1 = (r0 + 8 + carry >= 64) ? 0.f : s1.z;
    pin(acc);
    STAMPW(1);
    const GeluK gk = gelu_k(mu0, mu1, rs0, rs1);
    float2 cs[10];
#pragma unroll
    for (int j = 0; j < 10; j++) cs[j] = lds_f2(CS1 + (lane & 3) * 8 + (j < 8 ? ga * 128 + j * 32 : gs * 128 + wg * 64 + (j - 8) * 32));
#pragma unroll
    for (int j = 0; j < 5; j++) {
      gelu_unit(&acc[8 * j], gk, cs[2 * j], cs[2 * j + 1], j < 4 ? (ga + (j >> 1)) * 4096 + ((j & 1) ? dB_ : dA_) : gs * 4096 + (wg ? dB_ : dA_));
    }
    staged(B_H2, lane);
    STAMPW(2);
  }
  if (nyq) { const int o = (k1 + 64 * k2) * 321 + 320; nr = ldg_nc_u16(P.pwr + o); ni = ldg_nc_u16(P.pwi + o); }
  uint32_t E[16];
  {
    const int u = 32 * wg + k2;
    const float ng = (u & 1) ? -1.f : 1.f;
#pragma unroll
    for (int i = 0; i < 4; i++) {
      const int a = 8 * i + 2 * (lane & 3), v = u * a + 32;
      const float a0 = (float)((v & 63) - 32) * 0.09817477042468103f, a1 = (float)(((v + u) & 63) - 32) * 0.09817477042468103f;
      const float c0 = __cosf(a0), c1 = __cosf(a1), s0 = __sinf(a0), s1 = __sinf(a1);
      const float r0_ = __uint_as_float(lds_u32(ROW + 4 + a * 16)), r1_ = __uint_as_float(lds_u32(ROW + 20 + a * 16));
      const float r2_ = ng * __uint_as_float(lds_u32(ROW + 516 + a * 16)), r3_ = ng * __uint_as_float(lds_u32(ROW + 532 + a * 16));
      E[2 * i] = pack2(c0 * r0_, c1 * r1_); E[2 * i + 1] = pack2(s0 * r0_, s1 * r1_);
      E[8 + 2 * i] = pack2(c0 * r2_, c1 * r3_); E[9 + 2 * i] = pack2(s0 * r2_, s1 * r3_);
    }
    landed(E[0] ^ E[7] ^ E[9] ^ E[15]);
  }
    {
      const uint32_t a = STG + k2 * 352 + ((((k1 & 15) + wg) >> 1) + (lane & 3)) * 4, se = ((k1 ^ wg) & 1) ? 0x7632 : 0x5410;
      mbar_wait(B_CS, 0);
      STAMPW(77);
#pragma unroll
      for (int j = 0; j < 20; j++) {
        const uint32_t ad = a + j * 16 + (j < 16 ? wg * 64 : wg * -256);
        wf[j] = __byte_perm(lds_u32(ad), lds_u32(ad + 11264), se);
      }
      if (nyq) wf[0] = pack2(0.5f * bf_lo(nr), 0.5f * bf_lo(ni));
      landed(wf[19] ^ wf[18] ^ wf[15]);
      STAMPW(36);
    }
  {
    float acc[80];
    nb_sync(NB_F1, 384);
    wg_fence();
    wg_rs_160<0, 1, H128>(acc, E[0], E[1], E[2], E[3], dlo(FB, 8192));
    wg_rs_160<1, 1, H128>(acc, E[4], E[5], E[6], E[7], dlo(FB, 8192) + 128);
    wg_rs_160<1, 1, H128>(acc, E[8], E[9], E[10], E[11], dlo(FB, 8192) + 256);
    wg_rs_160<1, 1, H128>(acc, E[12], E[13], E[14], E[15], dlo(FB, 8192) + 384);
    wg_commit(); wg_wait<0>();
    pin(acc);
    uint32_t o[20];
#pragma unroll
    for (int i = 0; i < 20; i++) o[i] = pack2(acc[4 * i] + acc[4 * i + 3], acc[4 * i + 1] - acc[4 * i + 2]);
    nb_sync(NB_MLP, 256);
    const uint32_t vb = FB + (32 * wg + 8 * w + (lane & 7)) * 128, vx = ((lane & 7) ^ (lane >> 3)) << 4;
#pragma unroll
    for (int j = 0; j < 5; j++) stsm4(vb + (j >> 1) * 8192 + (vx ^ ((j & 1) << 6)), o[4 * j], o[4 * j + 1], o[4 * j + 2], o[4 * j + 3]);
    fence_async_smem();
    nb_arrive(NB_T2, 288);
    STAMPW(35);
  }
  s = 16 % NST;
  {
    float acc[40];
    const float ra = __uint_as_float(lds_u32(ROW + 4 + r0 * 16)), rb = __uint_as_float(lds_u32(ROW + 132 + r0 * 16));
#pragma unroll 1
    for (int it = 0; it < 10; it++) {
      STAGE_WAIT();
      if (it == 0) { STAMPW(3); GSTAMP(17); }
#pragma unroll
      for (int kk = 0; kk < 4; kk++) wg_ss_80<1, H64, H128>(acc, dA + so + (kk >> 1) * 256 + (kk & 1) * 2, (kk < 2 ? dBlo : dBhi) + so + (kk & 1) * 128, kk ? 1 : it);
      STAGE_NEXT();
    }
    STAGE_END();
    pin(acc);
    STAMPW(4); GSTAMP(18);
    const float n0 = -mu0 * ra, n1 = -mu1 * rb;
#pragma unroll
    for (int j = 0; j < 5; j++) {
#pragma unroll
      for (int f = 4 * j; f < 4 * j + 4; f++) {
        const float r_ = (f & 1) ? rb : ra, n_ = (f & 1) ? n1 : n0;
        yv[f] = pack2(fmaf(bf_lo(xf[f]), r_, n_) + acc[2 * f], fmaf(bf_hi(xf[f]), r_, n_) + acc[2 * f + 1]);
      }
      stsm4(STG + j * 4096 + (wg ? oB : oA), yv[4 * j], yv[4 * j + 1], yv[4 * j + 2], yv[4 * j + 3]);
    }
    staged(B_H2, lane);
    STAMPW(5);
    float s0 = 0.f, s1 = 0.f, v0 = 0.f, v1 = 0.f;
#pragma unroll
    for (int j = 0; j < 10; j++) {
      pin1(yv[2 * j]); pin1(yv[2 * j + 1]);
      const float a0 = bf_lo(yv[2 * j]), a1 = bf_hi(yv[2 * j]), a2 = bf_lo(yv[2 * j + 1]), a3 = bf_hi(yv[2 * j + 1]);
      s0 += a0 + a1; s1 += a2 + a3; v0 = fmaf(a0, a0, fmaf(a1, a1, v0)); v1 = fmaf(a2, a2, fmaf(a3, a3, v1));
    }
#pragma unroll
    for (int o = 1; o < 4; o <<= 1) {
      s0 += __shfl_xor_sync(~0u, s0, o); s1 += __shfl_xor_sync(~0u, s1, o); v0 += __shfl_xor_sync(~0u, v0, o); v1 += __shfl_xor_sync(~0u, v1, o);
    }
    if ((lane & 3) == 0) { sts_f2(ST1 + wg * 512 + r0 * 8, s0, v0); sts_f2(ST1 + 64 + wg * 512 + r0 * 8, s1, v1); }
    fence_async_smem();
    nb_arrive(NB_RDY, 288);
  }
  {
    const uint32_t dV = dlo(FB, 4096) + wg * 768;
    const uint32_t vb = FB + wg * 12288 + (8 * w + (lane & 7)) * 128, vx = ((lane & 7) ^ (lane >> 3)) << 4;
    mbar_wait(B_FFT, 0);
    STAMPW(38);
#pragma unroll
    for (int ps = 0; ps < 2; ps++) {
      float ac0[64], ac1[16];
      const uint4 d0 = lds_u4((ps ? DFR + 2048 : DF0) + (tid & 127) * 16), d1 = lds_u4(DFR + ps * 4096 + (tid & 127) * 16);
      const uint32_t D[8] = {d0.x, d0.y, d0.z, d0.w, d1.x, d1.y, d1.z, d1.w};
      wg_fence();
      wg_rs_128<0, 1, H128>(ac0, D[0], D[1], D[2], D[3], dV);
      wg_rs_128<1, 1, H128>(ac0, D[4], D[5], D[6], D[7], dV + 128);
      wg_rs_32<0, 1, H128>(ac1, D[0], D[1], D[2], D[3], dlo(FB + 8192, 4096) + wg * 4);
      wg_rs_32<1, 1, H128>(ac1, D[4], D[5], D[6], D[7], dlo(FB + 8192, 4096) + 128 + wg * 4);
      wg_commit(); wg_wait<0>();
      pin(ac0); pin(ac1);
      nb_sync(NB_WG0 + wg, 128);
#pragma unroll
      for (int j = 0; j < 5; j++) {
        uint32_t o[4];
#pragma unroll
        for (int u = 0; u < 4; u++) {
          const float* a = j < 4 ? &ac0[16 * j + 4 * u] : &ac1[4 * u];
          if (ps == 0) {
            const float xr = a[0] + a[3], xi = a[1] - a[2], wr = bf_lo(wf[4 * j + u]), wi = bf_hi(wf[4 * j + u]);
            o[u] = pack2(xr * wr - xi * wi, xr * wi + xi * wr);
          } else o[u] = pack2(a[0] - a[3], a[1] + a[2]);
        }
        stsm4(j < 4 ? vb + (j >> 1) * 4096 + (vx ^ ((j & 1) << 6)) : vb + 8192 - wg * 12288 + (vx ^ (wg << 6)), o[0], o[1], o[2], o[3]);
      }
      fence_async_smem();
      if (ps == 0) nb_sync(NB_WG0 + wg, 128);
    }
    STAMPW(39);
  }
  {
    float ac3[96];
    const uint32_t dA3 = dA + wg * 256;
    constexpr uint32_t dB = dlo(SM + 8192, 2048);
    mbar_wait(B_FM + s * 8, (phM >> s) & 1);
    nb_arrive(NB_T2, 288);
    STAMPW(6); GSTAMP(19);
    float m0, m1, rs0, rs1;
    float2 pa0, pa1, pb0, pb1;
    pa0.x = pa0.y = 0.f; pa1 = pb0 = pb1 = pa0;
#pragma unroll 1
    for (int it = 0; it < 20; it++) {
      STAGE_WAIT();
      wg_ss_192<1, H64, H128>(ac3, dA3 + so, dB + so, it);
      wg_ss_192<1, H64, H128>(ac3, dA3 + so + 2, dB + so + 384, 1);
      STAGE_NEXT();
      if (it == 18) {
        mbar_wait(B_ROW, 1);
        const uint32_t sa = STP + wg * 4096 + (lane & 3) * 1024 + r0 * 8;
        pa0 = lds_f2(sa); pa1 = lds_f2(sa + 512); pb0 = lds_f2(sa + 64); pb1 = lds_f2(sa + 576);
      }
    }
    m0 = pa0.x + pa1.x; m1 = pb0.x + pb1.x;
    float v0 = pa0.y + pa1.y, v1 = pb0.y + pb1.y;
#pragma unroll
    for (int o = 1; o < 4; o <<= 1) {
      m0 += __shfl_xor_sync(~0u, m0, o); m1 += __shfl_xor_sync(~0u, m1, o); v0 += __shfl_xor_sync(~0u, v0, o); v1 += __shfl_xor_sync(~0u, v1, o);
    }
    m0 *= 1.f / 640.f; m1 *= 1.f / 640.f;
    rs0 = rsq(fmaxf(fmaf(-m0, m0, v0 * (1.f / 640.f)), 0.f) + 1e-5f); rs1 = rsq(fmaxf(fmaf(-m1, m1, v1 * (1.f / 640.f)), 0.f) + 1e-5f);
    const GeluK gk = gelu_k(m0, m1, rs0, rs1);
    landed(__float_as_uint(gk.a1) ^ __float_as_uint(gk.b1));
    STAGE_END();
    STAMPW(7); GSTAMP(20);
    pin(ac3);
#pragma unroll 1
    for (int r = 0; r < 2; r++) {
      float2 cs[12];
#pragma unroll
      for (int j = 0; j < 4; j++) cs[j] = lds_f2(CS3 + r * 384 + j * 32 + (lane & 3) * 8);
#pragma unroll
      for (int h = 0; h < 3; h++) {
        const uint32_t buf = STG + r * 24576 + h * 8192 + wg * 4096;
        if (h < 2) {
#pragma unroll
          for (int j = 4 * h + 4; j < 4 * h + 8; j++) cs[j] = lds_f2(CS3 + r * 384 + j * 32 + (lane & 3) * 8);
        }
        if (h == 2) mbar_wait(B_H2, 0);
        gelu_unit(&ac3[16 * h], gk, cs[4 * h], cs[4 * h + 1], buf + oA);
        gelu_unit(&ac3[16 * h + 8], gk, cs[4 * h + 2], cs[4 * h + 3], buf + oB);
        staged(B_H2 + (3 * r + h) * 8, lane);
      }
      if (r) break;
#pragma unroll
      for (int i = 0; i < 48; i++) ac3[i] = ac3[i + 48];
      mbar_wait(B_YD, 0);
    }
    STAMPW(8);
  }
  {
  float acc[40];
#pragma unroll 1
  for (int it = 0; it < 24; it++) {
    STAGE_WAIT();
    if (it == 0) { STAMPW(9); GSTAMP(21); }
#pragma unroll
    for (int kk = 0; kk < 4; kk++) wg_ss_80<1, H64, H128>(acc, dA + so + (kk >> 1) * 256 + (kk & 1) * 2, (kk < 2 ? dBlo : dBhi) + so + (kk & 1) * 128, kk ? 1 : it);
    STAGE_NEXT();
  }
  STAGE_END();
  pin(acc);
#pragma unroll
  for (int i = 0; i < 20; i++) { asm volatile("mov.b32 %0, %0;" : "+r"(xf[i])); asm volatile("mov.b32 %0, %0;" : "+r"(yv[i])); }
  STAMPW(10); GSTAMP(22);
#pragma unroll
  for (int f = 0; f < 20; f++) { acc[2 * f] = silu(bf_lo(yv[f]) + acc[2 * f]); acc[2 * f + 1] = silu(bf_hi(yv[f]) + acc[2 * f + 1]); }
  {
    float z = 0.f;
#pragma unroll
    for (int f = 0; f < 40; f += 2) z = fmaf(acc[f], acc[f + 1], z);
    landed(__float_as_uint(z));
  }
  STAMPW(13);
  nb_sync(NB_S, 384);
  STAMPW(14);
#pragma unroll
  for (int j = 0; j < 5; j++) {
    uint32_t sv[4], o[4];
    const uint32_t ot = j < 4 ? wg * 8192 + o128 + (x128 ^ (j << 5)) : 16384 + wg * 2048 + srow * 32 + ((schk ^ ((srow >> 2) & 1)) << 4);
    ldsm4(FB + (j < 4 ? ot : 16384 + o128 + (x128 ^ (wg << 5))), sv[0], sv[1], sv[2], sv[3]);
#pragma unroll
    for (int u = 0; u < 4; u++) {
      const int f = 4 * j + u;
      o[u] = pack2(fmaf(bf_lo(sv[u]), acc[2 * f], bf_lo(xf[f])), fmaf(bf_hi(sv[u]), acc[2 * f + 1], bf_hi(xf[f])));
    }
    stsm4(STG + ot, o[0], o[1], o[2], o[3]);
  }
  fence_async_smem();
  nb_arrive(NB_RDY, 288);
  STAMPW(11); GSTAMP(23);
  }
#undef STAGE_WAIT
#undef STAGE_NEXT
#undef STAGE_END
}

DEVI void e_frags(uint32_t (&Cf)[16], uint32_t (&Sf)[16], int r0, int lane) {
  const float sc = 2.f / (2048.f * 640.f);
  const uint32_t sneg = 0x80008000u;
#pragma unroll
  for (int i = 0; i < 4; i++) {
    const int row = r0 + 8 * (i & 1), i0 = row * (8 * (i >> 1) + 2 * (lane & 3)) + 32;
    const float a0 = (float)((i0 & 63) - 32) * 0.09817477042468103f, a1 = (float)(((i0 + row) & 63) - 32) * 0.09817477042468103f;
    Cf[i] = pack2(sc * __cosf(a0), sc * __cosf(a1)); Sf[i] = pack2(sc * __sinf(a0), sc * __sinf(a1));
  }
  const bool sw = r0 & 1;
  const uint32_t N = 0x80008000u, m1 = sw ? N : 0u;
  const uint32_t nc = ((r0 + 1) & 2) ? N : 0u, ns = ((r0 & 2) ? N : 0u) ^ sneg;
#pragma unroll
  for (int i = 0; i < 4; i++) {
    Cf[4 + i] = (sw ? Sf[i] : Cf[i]) ^ nc; Sf[4 + i] = (sw ? Cf[i] : Sf[i]) ^ ns;
    Sf[i] ^= sneg;
    Cf[8 + i] = Cf[i] ^ m1; Sf[8 + i] = Sf[i] ^ m1; Cf[12 + i] = Cf[4 + i] ^ m1; Sf[12 + i] = Sf[4 + i] ^ m1;
  }
}
DEVI void s_step(const uint32_t (&Cf)[16], const uint32_t (&Sf)[16], int na, uint32_t sbase, uint32_t sx) {
#pragma unroll 1
  for (int i = 0; i < na; i++) {
    const uint32_t dU = dlo(FB, 8192) + i * 512;
    float p[32], r[32];
    wg_fence();
    wg_rs_64<0, 1, H128>(p, Cf[0], Cf[1], Cf[2], Cf[3], dU);
    wg_rs_64<0, 1, H128>(r, Sf[0], Sf[1], Sf[2], Sf[3], dU);
#pragma unroll
    for (int kk = 1; kk < 4; kk++) {
      wg_rs_64<1, 1, H128>(p, Cf[4 * kk], Cf[4 * kk + 1], Cf[4 * kk + 2], Cf[4 * kk + 3], dU + kk * 128);
      wg_rs_64<1, 1, H128>(r, Sf[4 * kk], Sf[4 * kk + 1], Sf[4 * kk + 2], Sf[4 * kk + 3], dU + kk * 128);
    }
    wg_commit(); wg_wait<0>();
    pin(p); pin(r);
    nb_sync(NB_WG2, 128);
#pragma unroll
    for (int j = 0; j < 4; j++) {
      uint32_t o[4];
#pragma unroll
      for (int u = 0; u < 4; u++) { const int f = 2 * (4 * j + u); o[u] = pack2(p[f] + r[f + 1], p[f + 1] - r[f]); }
      stsm4(sbase + i * 8192 + (sx ^ (j << 5)), o[0], o[1], o[2], o[3]);
    }
  }
  fence_async_smem();
  nb_arrive(NB_DMA, 160);
}

DEVI void fft_role(const Params& P, int slot, int w, uint32_t t_start) {
  const int b = slot >> 2, q = slot & 3, odd = q & 1;
  const int t = threadIdx.x & 127, lane = t & 31;
  const int r0 = 16 * w + (lane >> 2);
  const int srow = 16 * w + (lane & 7) + ((lane >> 3) & 1) * 8;
  const uint32_t sbase = FB + srow * 128, sx = ((srow & 7) ^ (lane >> 4)) << 4;

  uint32_t ep;
  {
    const __nv_bfloat16* p = P.px + (32 * (16 * q + (t >> 3)) + b) * 640 + 8 * (t & 7);
    uint4 ev[10];
    STAMPW(50);
    const int c0 = g1_chunk(b, 0);
    p += c0 * 64;
#pragma unroll
    for (int i = 0; i < 10; i++) { if (i + c0 == 10) p -= 640; ev[i] = ldg_nc_u4(p + i * 64); }
    {
      const int pc = min(t >> 3, 9), it = pc >= 5, rg = t & 7;
      const int cc = 5 * (b & 3) + pc - 5 * it;
      const uint32_t b0 = (cc < 16 ? SM + it * SLOT + 8192 + (cc >> 3) * 8192 : SM + it * SLOT + 24576) + sw128(rg, cc & 7);
      const uint32_t b1 = cc < 16 ? b0 + 4096 : FB + it * 4096 + sw128(rg, cc & 7);
      float c8[8];
      zero(c8);
      if (w < 3) {
        mbar_wait(B_FM + (w ? 8 : 0), 0);
        if (w == 1) mbar_wait(B_FM, 0);
#pragma unroll 1
        for (int hf = 0; hf < 2; hf++) {
#pragma unroll
          for (int i = 0; i < 4; i++) acc8(c8, lds_u4((hf ? b1 : b0) + i * 1024));
        }
        landed(__float_as_uint(c8[0]));
        if (lane == 0) mbar_arrive(B_CSR);
      }
#pragma unroll
      for (int i = 0; i < 4; i++) { const bool up = lane & 4; const float o = __shfl_xor_sync(~0u, up ? c8[i] : c8[i + 4], 4); c8[i] = (up ? c8[i + 4] : c8[i]) + o; }
#pragma unroll
      for (int i = 0; i < 2; i++) { const bool up = lane & 2; const float o = __shfl_xor_sync(~0u, up ? c8[i] : c8[i + 2], 2); c8[i] = (up ? c8[i + 2] : c8[i]) + o; }
      { const bool up = lane & 1; const float o = __shfl_xor_sync(~0u, up ? c8[0] : c8[1], 1); c8[0] = (up ? c8[1] : c8[0]) + o; }
      const int col = 160 * q + 8 * (odd ? (cc >= 16 ? cc - 16 : cc + 4) : cc) + rg;
      mbar_wait(B_EP, 0);
      ep = lds_u32(EPO);
      if (t < ((b & 12) == 12 ? 80 : 40))
        asm volatile("st.relaxed.gpu.global.u32 [%0], %1;" ::"l"(SC(cs1, (g1_chunk(b, it) * 640 + col) * 4)), "r"((__float_as_uint(c8[0]) & ~1u) | (ep & 1)) : "memory");
      __syncwarp();
    }
    STAMPW(32);
    float c[4], d[4];
    zero(c); zero(d);
#pragma unroll 1
    for (int hf = 0; hf < 2; hf++) {
#pragma unroll
      for (int i = 0; i < 5; i++) {
        const uint32_t e[4] = {ev[i].x, ev[i].y, ev[i].z, ev[i].w};
#pragma unroll
        for (int k = 0; k < 4; k++) {
          const float lo = bf_lo(e[k]), hi = bf_hi(e[k]);
          c[k] += lo + hi; d[k] = fmaf(lo, lo, fmaf(hi, hi, d[k]));
        }
        ev[i] = ev[i + 5];
      }
    }
    float a = (c[0] + c[1]) + (c[2] + c[3]), g = (d[0] + d[1]) + (d[2] + d[3]);
#pragma unroll
    for (int o = 1; o < 8; o <<= 1) { a += __shfl_xor_sync(~0u, a, o); g += __shfl_xor_sync(~0u, g, o); }
    const float m = a * (1.f / 640.f), var = fmaxf(fmaf(-m, m, g * (1.f / 640.f)), 0.f), r1 = rsq(var + 1e-5f);
    if ((t & 7) == 0)
      asm volatile("st.relaxed.gpu.global.v4.f32 [%0], {%1,%2,%3,%4};" ::"l"(SC(row, (slot * 16 + (t >> 3)) * 16)), "f"(m), "f"(r1),
                   "f"(r1 * rsq(var * r1 * r1 + 1e-5f)), "f"(__uint_as_float(ep)) : "memory");
    __syncwarp();
    STAMPW(78);
  }
  {
    {
      {
        const float* csp = (const float*)SC(cs1, 640 * q + 8 * min(t, 79));
        float x, y;
        int n = 0;
        bool again;
#pragma unroll 1
        do {
          uint2 cp[10];
#pragma unroll
          for (int k = 0; k < 10; k++) asm volatile("ld.relaxed.gpu.global.v2.u32 {%0,%1}, [%2];" : "=r"(cp[k].x), "=r"(cp[k].y) : "l"(csp + k * 640) : "memory");
          uint32_t o = 0, a = ~0u;
          x = y = 0.f;
#pragma unroll
          for (int k = 0; k < 10; k++) { o |= cp[k].x | cp[k].y; a &= cp[k].x & cp[k].y; x += __uint_as_float(cp[k].x); y += __uint_as_float(cp[k].y); }
          again = __any_sync(~0u, ((o ^ ep) | (a ^ ep)) & 1);
        } while (again && ++n < SPIN_MAX);
        if (again) __trap();
        if (t < 80) sts_f2(CS1 + t * 8, x, y);
        __syncwarp();
        nb_arrive(NB_STATS, 416);
        STAMPW(29);
      }
      mbar_wait(B_ROW, 0);
      const float mu0 = __uint_as_float(lds_u32(ROW + r0 * 16)), mu1 = __uint_as_float(lds_u32(ROW + 128 + r0 * 16));
      mbar_wait(B_FF + 4 * 8, 0);
#pragma unroll 1
      for (int j = 0; j < (G0M ? 3 : 5); j++) {
        mbar_wait(B_EM + (j ? j - 1 : 5) * 8, j > 0);
        if (j == 2 || j == 3) mbar_wait(B_FF + (j == 2 ? 5 : 1) * 8, 0);
        if (j == 0) STAMPW(66);
        fold(b, j, srow * 128, sx, mu0, mu1, odd);
      }
      fence_async_smem();
      float acc[80];
      if (G0M) nb_sync(NB_FOLD, 384); else nb_sync(NB_WG2, 128);
      STAMPW(33);
      uint32_t s = 5, sp = 4;
#pragma unroll 1
      for (int it = 0; it < 5; it++) {
        const uint32_t a = dlo(SM, 16) + s * SL16;
        mbar_wait(B_FF + s * 8, 0);
        wg_fence();
#pragma unroll
        for (int kk = 0; kk < 4; kk++) wg_ss_160<0, H128, H128>(acc, a + 2 * kk, a + 512 + 2 * kk, kk ? 1 : it);
        wg_commit();
        wg_wait<1>();
        if (t == 0) mbar_arrive_n(B_EM + sp * 8, 2);
        sp = s; s = s == NST - 1 ? 0 : s + 1;
      }
      wg_wait<0>();
      if (t == 0) mbar_arrive_n(B_EM + 3 * 8, 2);
      pin(acc);
      STAMPW(34);
#pragma unroll
      for (int j = 0; j < 10; j++) {
        const float* a = &acc[j * 8];
        stsm4(sbase + (j >> 2) * 8192 + (sx ^ ((j & 3) << 5)), pack2(a[0], a[1]), pack2(a[2], a[3]), pack2(a[4], a[5]), pack2(a[6], a[7]));
      }
      fence_async_smem();
      nb_arrive(NB_F1, 384);
      STAMPW(76);
    }
  }
  {
    const int k1 = slot >> 1, u = 8 * w + (lane >> 2);
#pragma unroll 1
    for (int ps = 0; ps < 2; ps++) {
      uint32_t D[8];
      d_frags(D, ps ? u * k1 : 0, ps ? 64 * u : k1 + 64 * u, lane);
      sts_u4((ps ? DFR + 2048 : DF0) + t * 16, D[0], D[1], D[2], D[3]); sts_u4(DFR + ps * 4096 + t * 16, D[4], D[5], D[6], D[7]);
    }
    __syncwarp();
    if (lane == 0) mbar_arrive(B_FFT);
  }
  {
    uint32_t Cf[16], Sf[16];
    e_frags(Cf, Sf, r0, lane);
    mbar_wait(B_U, 0);
    STAMPW(42);
    s_step(Cf, Sf, 3 - odd, sbase, sx);
    STAMPW(43);
  }
  {
    float p[40], r[40];
    uint32_t s = 70 % NST;
#pragma unroll 1
    for (int j = 0; j < 5; j++) {
      const uint32_t a0 = dlo(SM, 16) + s * SL16, a1 = dlo(STG, 16) + j * 512, b0 = a0 + 512, b1 = b0 + 640;
      const uint32_t ap = j < 4 ? a0 + 4 : a1, bp = j < 4 ? b0 + 4 : b1, aq = j < 4 ? a1 : a0 + 4, bq = j < 4 ? b1 : b0 + 4;
      mbar_wait(B_FF + s * 8, 1);
      wg_fence();
      wg_ss_80<0, H128, H128>(p, a0, b0, j); wg_ss_80<0, H128, H128>(p, a0 + 2, b0 + 2, 1);
      wg_ss_80<0, H128, H128>(p, ap, bp, 1); wg_ss_80<0, H128, H128>(p, ap + 2, bp + 2, 1);
      wg_ss_80<0, H128, H128>(r, aq, bq, j); wg_ss_80<0, H128, H128>(r, aq + 2, bq + 2, 1);
      wg_ss_80<0, H128, H128>(r, a1 + 4, b1 + 4, 1); wg_ss_80<0, H128, H128>(r, a1 + 6, b1 + 6, 1);
      wg_commit();
      s = s == NST - 1 ? 0 : s + 1;
    }
    wg_wait<0>();
    nb_sync(NB_WG2, 128);
    pin(p); pin(r);
    STAMPW(45);
#pragma unroll
    for (int j = 0; j < 5; j++) {
      uint32_t o0[4], o1[4];
#pragma unroll
      for (int u = 0; u < 4; u++) {
        const int f = 8 * j + 2 * u;
        o0[u] = pack2(p[f] + r[f], p[f + 1] + r[f + 1]); o1[u] = pack2(p[f] - r[f], p[f + 1] - r[f + 1]);
      }
      stsm4(sbase + (j < 4 ? (sx ^ (j << 5)) : 16384 + sx), o0[0], o0[1], o0[2], o0[3]);
      stsm4(sbase + (j < 4 ? 8192 + (sx ^ (j << 5)) : 16384 + (sx ^ 32)), o1[0], o1[1], o1[2], o1[3]);
    }
  }
  nb_arrive(NB_S, 384);
}

DEVI void helper_role(const Params& P, int slot, int warp, uint32_t t_start) {
  const int tid = threadIdx.x, q = slot & 3;
  const int n2 = q == 3 ? 1 : 3;
  if (warp == 15) {
    uint32_t ep = 0;
    if (elect()) { bulk_st(SC(tab, 786432 + q * 8192), HTB, 8192); bulk_commit(); }
#pragma unroll 1
    for (int j = 0; j < 17; j++) {
      const int d = j == 1 ? 0 : j > 4 ? j - 4 : -1;
      if (d >= 0) nb_sync(3, 416);
      if (elect()) {
        if (d == 0 || d >= 11) { bulk_st(SC(rem, (d ? 6 * q + 3 * d - 23 : 3 * q) * 16384), SM + (d & 3) * 49152, (d ? 3 : n2) * 16384); bulk_commit(); }
        if (d == 10) { bulk_st(SC(cs3, q * 6144), HTB, 6144); bulk_commit(); }
        if (j == 4 || d == 10 || d == 12) { bulk_wait_all(); flag_add(P.sc, j == 4 ? F_W2 : d == 10 ? F_CS3 : F_W4); }
        if (j < 13) {
          const uint32_t mb = BAR + (j & 3) * 8, buf = SM + (j & 3) * 49152;
          mbar_arrive(mb); mbar_expect(mb, j ? 49152 : n2 * 16384);
          if (j == 0 || j > 10) {
#pragma unroll 1
            for (int u = 0; u < (j ? 3 : n2); u++) {
              const int t = 6 * q + 3 * (j - 11) + u;
              const int row = j ? 192 * (t & 7) + 64 * (t >> 3) : 64 * (3 * q + u);
              tma_ld2(buf + u * 16384, j ? &P.w4h : &P.w2h, mb, 256, row); tma_ld2(buf + u * 16384 + 8192, j ? &P.w4h : &P.w2h, mb, 576, row);
            }
          } else bulk_ld(buf, (const unsigned char*)P.pw3 + q * 491520 + (j - 1) * 49152, 49152, mb);
        }
        if (j == 0) { bulk_wait_all(); flag_add(P.sc, F_TAB); }
      }
      __syncwarp();
    }
    ep = ldg_u32(&P.sc->epoch[slot]) + 1;
    __syncwarp();
    if (elect()) P.sc->epoch[slot] = ep;
    flag_wait(P.sc, F_TAB, ep * 132);
    return;
  }
  if (warp >= 12) return;
  float c[8];
  zero(c);
  const uint32_t mo = ((tid >= 192 ? 7 * 192 : 0) + tid) * 16;
#pragma unroll 1
  for (int j = 0; j < 13; j++) {
    const uint32_t buf = SM + (j & 3) * 49152;
    mbar_wait(BAR + (j & 3) * 8, (j >> 2) & 1);
    if (j == 0 || j > 10) {
      const uint32_t bs = buf + (tid >> 7) * 16384;
      const int k0 = (tid & 127) >> 3, cc = tid & 7;
      uint4 v[8];
#pragma unroll
      for (int u = 0; u < 8; u++) v[u] = lds_u4(bs + (u & 1) * 8192 + sw128(k0 + 16 * (u >> 1), cc));
      landed(v[0].x ^ v[1].x ^ v[2].x ^ v[3].x ^ v[4].x ^ v[5].x ^ v[6].x ^ v[7].x);
      nb_sync(5, 384);
#pragma unroll
      for (int u = 0; u < 8; u++)
        sts_u4(bs + (cc >> 1) * 4096 + sw128(k0 + 16 * ((u >> 1) & 1), (u >> 2) * 4 + 2 * (u & 1) + (cc & 1)), v[u].x, v[u].y, v[u].z, v[u].w);
    } else {
#pragma unroll
      for (int i = 0; i < 8; i++) acc8(c, lds_u4(buf + mo + i * 3072));
      landed(__float_as_uint(c[0]));
      if (j == 10) {
        if (tid >= 192) { sts_f4(HTB + (tid - 192) * 32, c[0], c[1], c[2], c[3]); sts_f4(HTB + (tid - 192) * 32 + 16, c[4], c[5], c[6], c[7]); }
        nb_sync(5, 384);
        if (tid < 192) {
          const float4 a = lds_f4(HTB + tid * 32), d = lds_f4(HTB + tid * 32 + 16);
          sts_f4(HTB + tid * 32, c[0] + a.x, c[1] + a.y, c[2] + a.z, c[3] + a.w); sts_f4(HTB + tid * 32 + 16, c[4] + d.x, c[5] + d.y, c[6] + d.z, c[7] + d.w);
        }
      }
    }
    fence_async_smem();
    nb_sync(3, 416);
  }
}

DEVI void l2_trickle(const void* p, int n, int slot, int lane) {
  const char* a = (const char*)p + (uint32_t)(slot * n);
#pragma unroll 1
  for (int o = 0; o < n; o += 4096) { asm volatile("prefetch.global.L2 [%0];" ::"l"(a + (uint32_t)min(o + lane * 128, n - 1))); __nanosleep(100); }
}

template <int I0, int I1> DEVI void init_barriers() {
#pragma unroll
  for (int i = I0; i < I1; i++) mbar_init(BAR + i * 8, BAR + i * 8 < B_G1 ? 2 : BAR + i * 8 == B_CSR ? 3 : BAR + i * 8 == B_FFT ? 5 : BAR + i * 8 >= B_H2 ? 8 : 1);
  asm volatile("fence.mbarrier_init.release.cluster;" ::: "memory");
}

__global__ void __launch_bounds__(512, 1) fused_kernel(const __grid_constant__ Params P) {
  extern __shared__ __align__(1024) unsigned char smem_raw[];
  const int tid = threadIdx.x, lane = tid & 31;
  const int warp = __shfl_sync(~0u, tid >> 5, 0);
  const uint32_t t_start = 0;
  uint32_t nsm, smid;
  asm volatile("mov.u32 %0, %%nsmid;" : "=r"(nsm));
  asm volatile("mov.u32 %0, %%smid;" : "=r"(smid));
  const int ts = P.slot[min(smid, 131u)], slot = nsm == 132 ? ts : blockIdx.x;
  const int b = slot >> 2, q = slot & 3, odd = q & 1;

  const int blkA = (5 * q + 1) >> 1, colS = 160 * q + (odd ? 0 : 128);
  if (warp == 14 && elect()) { tmap_pf(&P.x); tmap_pf(&P.w1a); tmap_pf(&P.w1b); }
  if (warp == 12 && slot < 128) {
    STAMP(24);
    if (elect()) init_barriers<0, NPRE>();
    __syncwarp();
    nb_arrive(NB_GO, 448);
    if (elect()) {
#pragma unroll 1
      for (int it = 0; it < NPRE; it++) {
        const uint32_t dst = SM + it * SLOT, fb = B_FM + it * 8;
        mbar_arrive(fb); mbar_expect(fb, 28672);
        const int k0 = g1_chunk(b, it) * 64;
        tma_ld3(dst, &P.x, fb, k0, b, 0);
        tma_ld3(dst + 8192, &P.w1a, fb, 0, k0, blkA); tma_ld2(dst + 24576, &P.w1b, fb, colS, k0); tma_ld2(FB + it * 4096, &P.w1b, fb, colS, k0 + 32);
      }
    }
    __syncwarp();
    STAMP(72);
  }
  if (warp == 13 && slot < 128) {
    if (elect()) init_barriers<NPRE, NBAR>();
    __syncwarp();
    nb_arrive(NB_GO, 448); nb_arrive(NB_EP, 64);
    STAMP(46);
  }
  if (warp < 12 || slot >= 128) {
    {
      const int g = slot < 128 ? slot * 384 + tid : 49152 + (slot - 128) * 512 + tid;
      const int inv = g >= 25600, R = (g - (inv ? 25600 : 0)) >> 3;
      const int tq = R / 800, Rq = R - 800 * tq;
      const int kc = inv ? Rq / 80 : Rq / 160, r = Rq - kc * (inv ? 80 : 160);
      const int k0 = 64 * kc + 8 * ((g & 7) ^ (r & 7));
      const int rr = (tq & 1) ? (r >= 128 ? r - 128 : r + 32) : r;
      const int kq = k0 / 160;
      const int mf = 160 * (tq >> 1) + (rr & ~1) + (tq & 1), m = mf ? mf : 320;
      const int d = r < 64 ? 64 * tq + r : 192 + 16 * tq + r;
      const int m2 = 160 * (kq >> 1) + (k0 - 160 * kq) + (kq & 1) + 4;
      int S = 2 * (inv ? d : m);
      const int base = ((inv ? m2 * d : (k0 + 4) * m + (rr & 1) * 160) + 320) % 640 - 320;
      S -= S > 320 ? 640 : 0;
      const float bs = (float)base, Sf = (float)S, H = inv ? 160.f : (float)m;
      uint32_t v[4];
#pragma unroll
      for (int e = 0; e < 4; e++) {
        float lo = fmaf((float)(e - 2), Sf, bs);
        if (e == 0 && inv && k0 == 0) lo = (float)((d & 1) * 320);
        v[e] = pack2(__cosf(lo * 0.009817477042468103f), __cosf((lo + H) * 0.009817477042468103f));
      }
      sts_u4((slot < 128 ? STG : HTB) + tid * 16, v[0], v[1], v[2], v[3]);
      STAMP(27);
      fence_async_smem();
    }
  }
  if (warp < 12 || slot >= 128) {
    if (slot >= 128) {
      if (tid == 0) init_barriers<0, 8>();
      __syncthreads();
      helper_role(P, slot, warp, t_start);
    } else {
      nb_sync(NB_GO, 448);
      nb_arrive(NB_TAB, 416);
      if (warp == 0) STAMP(0);
      if (warp >= 4) {
        asm volatile("setmaxnreg.inc.sync.aligned.u32 176;");
        mlp_role(P, b, q, warp >> 3, warp & 3, t_start);
      } else {
        asm volatile("setmaxnreg.inc.sync.aligned.u32 136;");
        fft_role(P, slot, warp & 3, t_start);
      }
    }
  } else {
    asm volatile("setmaxnreg.dec.sync.aligned.u32 24;");
    uint32_t s = NPRE, ph = 1;
#define PSTEP(FULL_, bytes, ISSUE) { mbar_wait(B_EM + s * 8, ph); const uint32_t dst = SM + s * SLOT, fb = FULL_ + s * 8; \
      if (elect()) { mbar_expect(fb, bytes); ISSUE; } __syncwarp(); if (++s == NST) { s = 0; ph ^= 1; } }
    if (warp == 14) {
      STAMP(49);
      nb_sync(NB_TAB, 416);
      if (elect()) { bulk_st(SC(tab, slot * 6144), STG, 6144); bulk_commit(); bulk_wait_all(); flag_add(P.sc, F_TAB); }
      __syncwarp();
      STAMP(64);
      mbar_wait(B_EP, 0);
      const uint32_t ep = lds_u32(EPO);
      {
        float4 v, u;
        int n = 0;
        bool ok;
        const unsigned char* rp = SC(row, (b * 64 + lane) * 16);
#pragma unroll 1
        do {
          asm volatile("ld.relaxed.gpu.global.v4.f32 {%0,%1,%2,%3}, [%4];" : "=f"(v.x), "=f"(v.y), "=f"(v.z), "=f"(v.w) : "l"(rp) : "memory");
          asm volatile("ld.relaxed.gpu.global.v4.f32 {%0,%1,%2,%3}, [%4+512];" : "=f"(u.x), "=f"(u.y), "=f"(u.z), "=f"(u.w) : "l"(rp) : "memory");
          ok = __all_sync(~0u, __float_as_uint(v.w) == ep && __float_as_uint(u.w) == ep);
        } while (!ok && ++n < SPIN_MAX);
        if (!ok) __trap();
        sts_f4(ROW + lane * 16, v.x, v.y, v.z, v.w); sts_f4(ROW + 512 + lane * 16, u.x, u.y, u.z, u.w);
      }
      __syncwarp();
      if (elect()) mbar_arrive(B_ROW);
      STAMP(31);
      nb_arrive(NB_STATS, 416);
      l2_trickle(P.pw2, 6400, slot, lane);
#pragma unroll 1
      for (int jb = 0; jb < 2; jb++) {
        const int bd = (b + (q & 2 ? 2 : 1) * (odd ? -1 : 1)) & 31;
        unsigned char* d = keep(SC(h, (jb ? 2621440 + b * 81920 : bd * 81920) + q * 20480));
        mbar_wait(B_H2, jb);
        if (elect()) {
          bulk_st(d, STG, 20480);
          bulk_commit();
          if (jb == 0) {
            bulk_wait_read();
            mbar_expect(B_CS, 22528);
            const int x0 = ((slot >> 1) * 321 + 160 * (slot & 1)) & ~15;
            tma_ld2(STG, &P.wr, B_CS, x0, 0); tma_ld2(STG + 11264, &P.wi, B_CS, x0, 0);
          }
          bulk_wait_all();
          flag_add(P.sc, jb ? F_X1 + (b >> 2) : F_H + (bd >> 2));
        }
        __syncwarp();
        STAMP(58 + jb);
        if (jb) {
          nb_sync(NB_RDY, 288);
          if (elect()) { bulk_st(SC(st1, slot * 1024), ST1, 1024); bulk_commit(); bulk_wait_all(); flag_add(P.sc, F_ST + (b >> 1)); }
          __syncwarp();
        }
        if (jb == 0) { mbar_wait(B_CS, 0); l2_trickle(P.pw4, 15360, slot, lane); }
      }
      flag_wait(P.sc, F_ST + (b >> 1), ep * 8);
      flag_wait(P.sc, F_CS3, ep * 4);
      mbar_wait(B_G1, 1);
      if (elect()) {
        mbar_expect(B_CS, 3072 + 8192);
        bulk_ld(STP, SC(st1, (b & ~1) * 4096), 8192, B_CS);
#pragma unroll 1
        for (int u = 0; u < 4; u++) bulk_ld(CSP + u * 768, SC(cs3, u * 6144 + (2 * q + (b & 1)) * 768), 768, B_CS);
      }
      mbar_wait(B_CS, 1);
#pragma unroll 1
      for (int i0 = 0; i0 < 768; i0 += 256) {
        const int i = i0 + lane * 8;
        const float2 a = lds_f2(CSP + i), c = lds_f2(CSP + 768 + i), d = lds_f2(CSP + 1536 + i), f = lds_f2(CSP + 2304 + i);
        sts_f2(CS3 + i, (a.x + c.x) + (d.x + f.x), (a.y + c.y) + (d.y + f.y));
      }
      STAMP(30);
      __syncwarp();
      if (elect()) mbar_arrive(B_ROW);
      __syncwarp();
      watch(P.sc, F_W4, ep * 4, 2);
#pragma unroll 1
      for (int j = 0; j < 6; j++) {
        unsigned char* d = keep(SC(h2, (b & ~1) * 196608 + (j >> 1) * 65536 + (2 * q + (b & 1)) * 8192 + (j & 1) * 4096));
        mbar_wait(B_H2 + j * 8, 0);
        if (elect()) {
          bulk_st(d, STG + j * 8192, 4096); bulk_st(d + 196608, STG + j * 8192 + 4096, 4096);
          bulk_commit();
          if (j == FLAGA) { asm volatile("cp.async.bulk.wait_group %0;" ::"n"(FLAGA - 1) : "memory"); flag_add(P.sc, F_H2 + (b >> 2)); }
        }
        __syncwarp();
        if (j == 0) STAMP(79);
        if (j == FLAGA) STAMP(60);
      }
      if (elect()) { bulk_wait_all(); flag_add(P.sc, F_H2 + 8 + (b >> 2)); }
      __syncwarp();
      STAMP(62);
      watch(P.sc, F_H2 + 8 + (b >> 2), ep * 16, 3);
      nb_sync(NB_RDY, 288);
      if (elect()) {
        tma_st4(&P.outa, STG, 64 * q, 0, 0, b); tma_st4(&P.outr, STG + 16384, 256 + 16 * q, 0, 0, b);
        bulk_commit(); bulk_wait_read();
      }
      __syncwarp();
      STAMP(63);
    } else if (warp == 15) {
      if ((uint32_t)__cvta_generic_to_shared(smem_raw) != SM) __trap();
      const uint32_t ep = ldg_u32(SC(epoch, slot * 4)) + 1;
      nb_sync(NB_EP, 64);
      if (elect()) { *(uint32_t*)SC(epoch, slot * 4) = ep; sts_u32(EPO, ep); mbar_arrive(B_EP); }
      __syncwarp();
      STAMP(74);
#pragma unroll 1
      for (int i = 3; i < 15; i++) tmap_pf(&P.x + i);
      watch(P.sc, F_TAB, ep * 132, 0);
      mbar_wait(B_FM + 5 * 8, 0);
#pragma unroll 1
      for (int a = 0; a < 3; a++) l2_trickle(a == 2 ? P.pw3 : a ? P.pwi : P.pwr, a == 2 ? 15360 : 10272, slot, lane);
      STAMP(28);
      watch(P.sc, F_W2, ep * 4, 1);
      const int k1 = slot >> 1, hh = slot & 1;
      nb_sync(NB_T2, 288);
      if (elect()) {
        tma_st4(&P.t1h, FB + 16384, 0, 0, 5 * q + (odd ? 0 : 4), b);
#pragma unroll 1
        for (int i = 0; i < 4; i++) {
          const uint32_t t0 = (uint32_t)clock64();
          while (i >= T1FREE && (uint32_t)clock64() - t0 < T1GAP) {}
          tma_st4(&P.t1a, FB + i * 4096, 0, 32 * (i & 1), blkA + (i >> 1), b);
        }
        bulk_commit();
        bulk_wait_all(); flag_add(P.sc, F_T1 + (q >> 1));
      }
      __syncwarp();
      STAMP(75);
      flag_wait(P.sc, F_T1 + hh, ep * 64);
      STAMP(37);
      if (elect()) { mbar_expect(B_FFT, 20480); tma_ld3(FB, &P.t1l, B_FFT, 0, k1 * 32, 5 * hh); }
      nb_sync(NB_T2, 288);
      if (elect()) { tma_st4(&P.t2s, FB, 0, 0, 5 * hh, k1); bulk_commit(); bulk_wait_all(); flag_add(P.sc, F_T2 + hh); mbar_arrive(B_G1); }
      __syncwarp();
      STAMP(40);
      flag_wait(P.sc, F_T2 + (q >> 1), ep * 64);
      STAMP(41);
      if (elect()) {
        mbar_expect(B_U, (3 - odd) * 8192);
#pragma unroll 1
        for (int i = 0; i < 3 - odd; i++) tma_ld2(FB + i * 8192, &P.t2l, B_U, (blkA + i) * 64, b * 64);
      }
      unsigned char* yd = keep(SC(Y, (b * 10 + blkA) * 8192));
      nb_sync(NB_DMA, 160);
      if (elect()) { bulk_st(yd, FB, (3 - odd) * 8192); bulk_commit(); bulk_wait_all(); flag_add(P.sc, F_Y + (b >> 2)); mbar_arrive(B_YD); }
      __syncwarp();
      STAMP(44);
      watch(P.sc, F_Y + (b >> 2), ep * 16, 4);
      STAMP(54);
    } else if (warp == 13) {
      nb_sync(NB_INIT, 64);
#pragma unroll 1
      for (int it = NPRE; it < 10; it++) PSTEP(B_FM, 8192, tma_ld3(dst, &P.x, fb, g1_chunk(b, it) * 64, b, 0));
      PSTEP(B_FF, 16384, mbar_arrive(fb); tma_ld3(dst + 8192, &P.x, fb, g1_chunk(b, 0) * 64, b, 0); tma_ld3(dst + 16384, &P.x, fb, g1_chunk(b, 1) * 64, b, 0));
#pragma unroll 1
      for (int it = 0; it < 5; it++)
        PSTEP(B_FF, (it & 5) ? 0 : 8192, (void)dst; if (!(it & 5)) tma_ld3(FB + (s - 1) * 4096, &P.x, fb, g1_chunk(b, 2 + (it >> 1)) * 64, b, 0));
      mbar_wait(B_EP, 0);
      const uint32_t ep = lds_u32(EPO);
#pragma unroll 1
      for (int g = 0; g < 3; g++) {
        const unsigned char* src = SC(h, g == 0 ? b * 81920 : g == 1 ? 2621440 + (b & ~1) * 81920 : 5242880 + b * 196608);
        const int n = g == 0 ? 10 : g == 1 ? 20 : 24, step = g == 1 ? 4096 : 8192, o2 = g == 1 ? 81920 : 4096;
        flag_wait(P.sc, F_H + 8 * g + (b >> 2), ep * 16);
        if (g == 0 && elect()) mbar_arrive(B_G1);
        __syncwarp();
        STAMP(g == 2 ? 55 : 52 + g);
#pragma unroll 1
        for (int it = 0; it < n; it++) {
          if (g == 2 && it == 8) watched(3);
          PSTEP(B_FM, 8192, bulk_ld(dst, src, 4096, fb); bulk_ld(dst + 4096, src + o2, 4096, fb));
          src += step;
        }
      }
      const unsigned char* src = SC(Y, b * 81920);
      watched(4);
#pragma unroll 1
      for (int it = 0; it < 5; it++) PSTEP(B_FF, 16384, bulk_ld(dst, src + G5C(it) * 8192, 8192, fb); bulk_ld(STG + it * 8192, src + (G5C(it) + (it < 4 ? 3 : 5)) * 8192, 8192, fb));
    } else {
      nb_sync(NB_INIT, 64);
#pragma unroll 1
      for (int it = NPRE; it < 10; it++) {
        const int k0 = g1_chunk(b, it) * 64;
        if (it == NST) mbar_wait(B_CSR, 0);
        PSTEP(B_FM, 20480, tma_ld3(dst + 8192, &P.w1a, fb, 0, k0, blkA); tma_ld2(dst + 24576, &P.w1b, fb, colS, k0); tma_ld2(FB + s * 4096, &P.w1b, fb, colS, k0 + 32));
        if (it == 5) STAMP(73);
      }
      s = 5;
#pragma unroll 1
      for (int g = 0; g < 2; g++) {
        if (g == 0) watched(0);
        else {
#pragma unroll 1
          for (int m = 0; m < 2; m++) {
            watched(1 + m);
            if (m == 0) mbar_wait(B_G1, 0);
            const unsigned char* rem = SC(rem, q * 4096 + m * 163840);
#pragma unroll 1
            for (int it = 0; it < (m ? 24 : 10); it++) {
              PSTEP(B_FM, 20480, tma_ld3(dst + 8192, &P.w2a + m, fb, 64 * q, m ? 192 * (it & 7) + 64 * (it >> 3) : 64 * it, 0); bulk_ld(dst + 24576, rem, 4096, fb));
              rem += 16384;
            }
#pragma unroll 1
            for (int it = 0; it < (m ? 0 : 20); it++) {
              const int gr = it / 5, j = it - 5 * gr;
              PSTEP(B_FM, 12288, tma_ld4(dst + 8192, &P.w3, fb, 0, j < 4 ? 64 * gr + 16 * j : 256 + 16 * gr, 6 * q + 3 * (b & 1), 0));
            }
          }
        }
#pragma unroll 1
        for (int it = 0; it < 5; it++) {
          const int c = g1_chunk(b, it);
          const unsigned char* tp = SC(tab, q * 102400 + (g ? 40 + G5C(it) : c >= 5 ? 2 * c - 10 : 2 * c) * 10240);
          PSTEP(B_FF, 20480, bulk_ld(dst + 8192, tp, 10240, fb); bulk_ld(dst + 18432, tp + (g ? (it < 4 ? 3 : 5) : 1) * 10240, 10240, fb));
        }
      }
    }
#undef PSTEP
  }
}

typedef CUresult (*EncFn)(CUtensorMap*, CUtensorMapDataType, cuuint32_t, void*, const cuuint64_t*, const cuuint64_t*, const cuuint32_t*,
                          const cuuint32_t*, CUtensorMapInterleave, CUtensorMapSwizzle, CUtensorMapL2promotion, CUtensorMapFloatOOBfill);

static void enc(EncFn fn, CUtensorMap* m, const void* p, int rank, const cuuint64_t* dims, const cuuint64_t* strides, const cuuint32_t* box, int sw) {
  cuuint32_t es[5] = {1, 1, 1, 1, 1};
  fn(m, CU_TENSOR_MAP_DATA_TYPE_BFLOAT16, rank, (void*)p, dims, strides, box, es, CU_TENSOR_MAP_INTERLEAVE_NONE,
     sw == 128 ? CU_TENSOR_MAP_SWIZZLE_128B : sw == 32 ? CU_TENSOR_MAP_SWIZZLE_32B : CU_TENSOR_MAP_SWIZZLE_NONE, CU_TENSOR_MAP_L2_PROMOTION_L2_128B,
     CU_TENSOR_MAP_FLOAT_OOB_FILL_NONE);
}

extern "C" void kernel_launch(void* const* d_in, const int* in_sizes, int n_in, void* d_out, int out_size) {
  (void)in_sizes; (void)n_in; (void)out_size;
  void* fnp = nullptr;
  cudaDriverEntryPointQueryResult qr;
  cudaGetDriverEntryPoint("cuTensorMapEncodeTiled", &fnp, cudaEnableDefault, &qr);
  EncFn fn = (EncFn)fnp;
  Scratch* sc;
  cudaGetSymbolAddress((void**)&sc, g_sc);
  void *t1 = sc->T1, *t2 = sc->T2;

  Params P;
  P.sc = sc;
  P.px = (const __nv_bfloat16*)d_in[0]; P.pwr = (const __nv_bfloat16*)d_in[1]; P.pwi = (const __nv_bfloat16*)d_in[2];
  P.pw1 = (const __nv_bfloat16*)d_in[4]; P.pw2 = (const __nv_bfloat16*)d_in[5]; P.pw3 = (const __nv_bfloat16*)d_in[6]; P.pw4 = (const __nv_bfloat16*)d_in[7];
  { cuuint64_t d[3] = {640, 32, 64}, s[2] = {1280, 40960}; cuuint32_t bx[3] = {64, 1, 64}; enc(fn, &P.x, d_in[0], 3, d, s, bx, 128); }
  { cuuint64_t d[3] = {64, 640, 10}, s[2] = {1280, 128}; cuuint32_t bx[3] = {64, 64, 2}; enc(fn, &P.w1a, d_in[4], 3, d, s, bx, 128); }
  { cuuint64_t d[2] = {640, 640}, s[1] = {1280}; cuuint32_t bx[2] = {32, 32}; enc(fn, &P.w1b, d_in[4], 2, d, s, bx, 128); }
  { cuuint64_t d[3] = {320, 1536, 2}, s[2] = {1280, 640}; cuuint32_t bx[3] = {64, 64, 2}; enc(fn, &P.w4a, d_in[7], 3, d, s, bx, 128);
    d[1] = 640; enc(fn, &P.w2a, d_in[5], 3, d, s, bx, 128); }
  { cuuint64_t d[2] = {640, 640}, s[1] = {1280}; cuuint32_t bx[2] = {64, 64}; enc(fn, &P.w2h, d_in[5], 2, d, s, bx, 128); }
  { cuuint64_t d[2] = {640, 1536}, s[1] = {1280}; cuuint32_t bx[2] = {64, 64}; enc(fn, &P.w4h, d_in[7], 2, d, s, bx, 128); }
  { cuuint64_t d[2] = {20544, 32}, s[1] = {41088}; cuuint32_t bx[2] = {176, 32}; enc(fn, &P.wr, d_in[1], 2, d, s, bx, 0); enc(fn, &P.wi, d_in[2], 2, d, s, bx, 0); }
  { cuuint64_t d[4] = {64, 320, 24, 2}, s[3] = {3072, 128, 983040}; cuuint32_t bx[4] = {64, 16, 3, 2}; enc(fn, &P.w3, d_in[6], 4, d, s, bx, 128); }
  { cuuint64_t d[4] = {64, 64, 10, 32}, s[3] = {40960, 128, 1280}; cuuint32_t bx[4] = {64, 32, 1, 1}; enc(fn, &P.t1a, t1, 4, d, s, bx, 128); }
  { cuuint64_t d[4] = {32, 64, 20, 32}, s[3] = {40960, 64, 1280}; cuuint32_t bx[4] = {64, 64, 1, 1}; enc(fn, &P.t1h, t1, 4, d, s, bx, 128); }
  { cuuint64_t d[3] = {64, 2048, 10}, s[2] = {1280, 128}; cuuint32_t bx[3] = {64, 32, 5}; enc(fn, &P.t1l, t1, 3, d, s, bx, 128); }
  { cuuint64_t d[4] = {64, 32, 10, 64}, s[3] = {81920, 128, 1280}; cuuint32_t bx[4] = {64, 32, 5, 1}; enc(fn, &P.t2s, t2, 4, d, s, bx, 128); }
  { cuuint64_t d[2] = {640, 2048}, s[1] = {1280}; cuuint32_t bx[2] = {64, 64}; enc(fn, &P.t2l, t2, 2, d, s, bx, 128); }
  { cuuint64_t d[4] = {320, 64, 2, 32}, s[3] = {40960, 640, 1280}; cuuint32_t ba[4] = {64, 64, 2, 1}, br[4] = {16, 64, 2, 1};
    enc(fn, &P.outa, d_out, 4, d, s, ba, 128); enc(fn, &P.outr, d_out, 4, d, s, br, 32); }

  for (int i = 0; i < 132; i++) {
    const int u = i - 64;
    P.slot[i] = i < 64 ? ((i >> 1) & 7) * 16 + (i >> 4) * 2 + (i & 1) : i < 120 ? (1 + (u >> 1) % 7) * 16 + 8 + (u / 14) * 2 + (u & 1) : i < 124 ? i + 8 : i - 116;
  }
  cudaFuncSetAttribute(fused_kernel, cudaFuncAttributeMaxDynamicSharedMemorySize, SMEM_BYTES);
  fused_kernel<<<132, 512, SMEM_BYTES>>>(P);
}
```

```cpp
#include <cuda_runtime.h>
#include <cuda_bf16.h>
#include <cuda.h>
#include <stdint.h>
#include <stddef.h>

#define DEVI __device__ __forceinline__
#define NPRE_ 3

struct __align__(1024) Scratch {
  unsigned char tab[2 * 409600];
  unsigned char rem[34 * 16384];
  unsigned char h[32 * 20 * 4096];
  unsigned char x1[32 * 20 * 4096];
  unsigned char h2[32 * 48 * 4096];
  unsigned char Y[32 * 10 * 8192];
  __nv_bfloat16 T1[2048 * 640];
  __nv_bfloat16 T2[2048 * 640];
  float2 st1[32 * 8 * 64];
  float cs1[10 * 640];
  float cs3[4 * 1536];
  float4 row[2048];
  unsigned int flag[128 * 32];
  unsigned int epoch[160];
};
static_assert(offsetof(Scratch, x1) == offsetof(Scratch, h) + 2621440 && offsetof(Scratch, h2) == offsetof(Scratch, h) + 5242880, "layout");
__device__ Scratch g_sc;

enum { F_H = 0, F_X1 = 8, F_H2 = 16, F_Y = 48, F_TAB = 80, F_W2 = 81, F_W4 = 82, F_T1 = 83, F_T2 = 85, F_CS3 = 88, F_ST = 96 };

enum : uint32_t {
  NST = 6, SLOT = 28672, NPRE = NPRE_,
  SM = 1024,
  STG = SM + NST * SLOT,
  FB = STG + 24576,
  BAR = FB + 24576,
  ROW = BAR + 384,
  CS1 = ROW + 1024,
  CS3 = CS1 + 640,
  ST1 = CS3 + 768,
  DFR = ST1 + 1024,
  DF0 = STG + 22528,
  CSP = STG, STP = STG + 16384,
  EPO = DFR + 6144,
  PRF = EPO + 16,
  HTB = SM + 204800,
  SMEM_BYTES = PRF + 96 * 4 - SM,
  B_FM = BAR, B_FF = BAR + 48, B_EM = BAR + 96, B_G1 = BAR + 144, B_FFT = BAR + 152, B_ROW = BAR + 160, B_EP = BAR + 168, B_CS = BAR + 176,
  B_WT = BAR + 184,
  B_CSR = BAR + 232,
  B_U = BAR + 240, B_YD = BAR + 248,
  B_H2 = BAR + 256,
  NBAR = 38,
  H128 = 0x40000040u,
  H64 = 0x80000020u,
  SL16 = SLOT >> 4
};
enum { NB_WG2 = 1, NB_INIT = 2, NB_STATS = 3, NB_S = 4, NB_RDY = 5, NB_WG0 = 6, NB_T2 = 8, NB_GO = 10, NB_DMA = 11, NB_F1 = 12, NB_MLP = 13, NB_EP = 14, NB_TAB = 9, NB_FOLD = 15 };
__device__ __forceinline__ int g1_chunk(int b, int it) { const int c = (b >> 2) + (b >> 4) + it; return c >= 10 ? c - 10 : c; }
__host__ __device__ constexpr uint32_t dlo(uint32_t addr, uint32_t lbo) { return (addr >> 4) | ((lbo >> 4) << 16); }

struct Params {
  Scratch* sc;
  const __nv_bfloat16 *px, *pwr, *pwi, *pw1, *pw2, *pw3, *pw4;
  CUtensorMap x, w1a, w1b, wr, wi, w3, t1a, t1h, t1l, t2s, t2l, outa, outr, w2a, w4a, w2h, w4h;
  int slot[132];
};

#define SPIN_MAX 4000000
#define PGAP 100
#define G0M 0
#define G5C(j) ((0x26510 >> (4 * (j))) & 15)
#define FLAGA 5
#define T1GAP 500
#define T1FREE 2
DEVI void mbar_init(uint32_t b, int c) { asm volatile("mbarrier.init.shared::cta.b64 [%0], %1;" ::"r"(b), "r"(c)); }
DEVI void mbar_expect(uint32_t b, int bytes) { asm volatile("mbarrier.arrive.expect_tx.shared::cta.b64 _, [%0], %1;" ::"r"(b), "r"(bytes) : "memory"); }
DEVI void mbar_arrive(uint32_t b) { asm volatile("mbarrier.arrive.shared::cta.b64 _, [%0];" ::"r"(b) : "memory"); }
DEVI void mbar_arrive_n(uint32_t b, uint32_t n) { asm volatile("mbarrier.arrive.shared::cta.b64 _, [%0], %1;" ::"r"(b), "r"(n) : "memory"); }
DEVI void mbar_wait(uint32_t b, uint32_t par) {
  asm volatile("{\n.reg .pred p;\nL_%=:\nmbarrier.try_wait.parity.shared::cta.b64 p, [%0], %1;\n@!p bra.uni L_%=;\n}" ::"r"(b), "r"(par) : "memory");
}
DEVI bool elect() { uint32_t p; asm volatile("{\n.reg .pred P;\nelect.sync _|P, 0xffffffff;\nselp.u32 %0,1,0,P;\n}" : "=r"(p)); return p; }
DEVI void nb_sync(int id, int n) { asm volatile("bar.sync %0, %1;" ::"r"(id), "r"(n) : "memory"); }
DEVI void nb_arrive(int id, int n) { asm volatile("bar.arrive %0, %1;" ::"r"(id), "r"(n) : "memory"); }
DEVI void fence_async_smem() { asm volatile("fence.proxy.async.shared::cta;" ::: "memory"); }
DEVI void fence_async_gmem() { asm volatile("fence.proxy.async.global;" ::: "memory"); }
DEVI void bulk_ld(uint32_t dst, const void* src, int bytes, uint32_t bar) {
  asm volatile("cp.async.bulk.shared::cluster.global.mbarrier::complete_tx::bytes [%0], [%1], %2, [%3];" ::"r"(dst), "l"(src), "r"(bytes), "r"(bar) : "memory");
}
DEVI void bulk_st(void* dst, uint32_t src, int bytes) {
  asm volatile("cp.async.bulk.global.shared::cta.bulk_group [%0], [%1], %2;" ::"l"(dst), "r"(src), "r"(bytes) : "memory");
}
DEVI void tma_ld2(uint32_t dst, const CUtensorMap* m, uint32_t bar, int c0, int c1) {
  asm volatile("cp.async.bulk.tensor.2d.shared::cluster.global.mbarrier::complete_tx::bytes [%0], [%1, {%3, %4}], [%2];" ::"r"(dst), "l"(m), "r"(bar), "r"(c0), "r"(c1) : "memory");
}
DEVI void tma_ld3(uint32_t dst, const CUtensorMap* m, uint32_t bar, int c0, int c1, int c2) {
  asm volatile("cp.async.bulk.tensor.3d.shared::cluster.global.mbarrier::complete_tx::bytes [%0], [%1, {%3, %4, %5}], [%2];" ::"r"(dst), "l"(m), "r"(bar), "r"(c0), "r"(c1), "r"(c2) : "memory");
}
DEVI void tma_ld4(uint32_t dst, const CUtensorMap* m, uint32_t bar, int c0, int c1, int c2, int c3) {
  asm volatile("cp.async.bulk.tensor.4d.shared::cluster.global.mbarrier::complete_tx::bytes [%0], [%1, {%3, %4, %5, %6}], [%2];" ::"r"(dst), "l"(m), "r"(bar), "r"(c0), "r"(c1), "r"(c2), "r"(c3) : "memory");
}
DEVI void tma_st4(const CUtensorMap* m, uint32_t src, int c0, int c1, int c2, int c3) {
  asm volatile("cp.async.bulk.tensor.4d.global.shared::cta.bulk_group [%0, {%2, %3, %4, %5}], [%1];" ::"l"(m), "r"(src), "r"(c0), "r"(c1), "r"(c2), "r"(c3) : "memory");
}
DEVI void tmap_pf(const CUtensorMap* m) { asm volatile("prefetch.tensormap [%0];" ::"l"(m) : "memory"); }
DEVI void bulk_commit() { asm volatile("cp.async.bulk.commit_group;" ::: "memory"); }
DEVI void bulk_wait_read() { asm volatile("cp.async.bulk.wait_group.read 0;" ::: "memory"); }
DEVI void bulk_wait_all() { asm volatile("cp.async.bulk.wait_group 0;" ::: "memory"); }
#define SC(member, off) ((unsigned char*)P.sc + (uint32_t)(offsetof(Scratch, member) + (off)))
DEVI unsigned char* keep(unsigned char* p) { asm volatile("" : "+l"(p)); return p; }
DEVI unsigned char* flag_ptr(Scratch* sc, uint32_t f) { return (unsigned char*)sc + (uint32_t)(offsetof(Scratch, flag) + f * 128); }
DEVI void flag_add(Scratch* sc, uint32_t f) { asm volatile("red.relaxed.gpu.global.add.u32 [%0], 1;" ::"l"(flag_ptr(sc, f)) : "memory"); }
DEVI void flag_wait(Scratch* sc, uint32_t f, uint32_t target) {
  asm volatile("{\n.reg .pred p;\n.reg .u32 c, v;\nmov.u32 c, 0;\nL_%=:\nld.relaxed.gpu.global.u32 v, [%0];\nsub.u32 v, v, %1;\n"
               "setp.ge.s32 p, v, 0;\n@p bra.uni D_%=;\nadd.u32 c, c, 1;\nsetp.lt.u32 p, c, 4000000;\n@p bra.uni L_%=;\ntrap;\nD_%=:\n"
               "fence.proxy.async.global;\n}" ::"l"(flag_ptr(sc, f)), "r"(target) : "memory");
}
DEVI void flag_wait4(Scratch* sc, uint32_t f, uint32_t target) {
  asm volatile("{\n.reg .pred p;\n.reg .u32 c, t, u, v0, v1, v2, v3;\n"
               "ld.relaxed.gpu.global.u32 v0, [%0];\nmov.u32 t, %%clock;\nA_%=:\nmov.u32 u, %%clock;\nsub.u32 u, u, t;\nsetp.lt.u32 p, u, %2;\n@p bra.uni A_%=;\n"
               "ld.relaxed.gpu.global.u32 v1, [%0];\nmov.u32 t, %%clock;\nB_%=:\nmov.u32 u, %%clock;\nsub.u32 u, u, t;\nsetp.lt.u32 p, u, %2;\n@p bra.uni B_%=;\n"
               "ld.relaxed.gpu.global.u32 v2, [%0];\nmov.u32 t, %%clock;\nC_%=:\nmov.u32 u, %%clock;\nsub.u32 u, u, t;\nsetp.lt.u32 p, u, %2;\n@p bra.uni C_%=;\n"
               "ld.relaxed.gpu.global.u32 v3, [%0];\nmov.u32 c, 0;\nL_%=:\n"
               "sub.u32 u, v0, %1;\nsetp.ge.s32 p, u, 0;\n@p bra.uni D_%=;\nld.relaxed.gpu.global.u32 v0, [%0];\n"
               "sub.u32 u, v1, %1;\nsetp.ge.s32 p, u, 0;\n@p bra.uni D_%=;\nld.relaxed.gpu.global.u32 v1, [%0];\n"
               "sub.u32 u, v2, %1;\nsetp.ge.s32 p, u, 0;\n@p bra.uni D_%=;\nld.relaxed.gpu.global.u32 v2, [%0];\n"
               "sub.u32 u, v3, %1;\nsetp.ge.s32 p, u, 0;\n@p bra.uni D_%=;\nld.relaxed.gpu.global.u32 v3, [%0];\n"
               "add.u32 c, c, 1;\nsetp.lt.u32 p, c, 4000000;\n@p bra.uni L_%=;\ntrap;\nD_%=:\n"
               "fence.proxy.async.global;\n}" ::"l"(flag_ptr(sc, f)), "r"(target), "n"(PGAP) : "memory");
}
DEVI void watch(Scratch* sc, uint32_t f, uint32_t target, int k) { flag_wait(sc, f, target); if (elect()) mbar_arrive(B_WT + k * 8); __syncwarp(); }
DEVI void watched(int k) { mbar_wait(B_WT + k * 8, 0); fence_async_gmem(); }
DEVI void wg_fence() { asm volatile("wgmma.fence.sync.aligned;" ::: "memory"); }
DEVI void wg_commit() { asm volatile("wgmma.commit_group.sync.aligned;" ::: "memory"); }
template <int N> DEVI void wg_wait() { asm volatile("wgmma.wait_group.sync.aligned %0;" ::"n"(N) : "memory"); }
DEVI void stsm4(uint32_t a, uint32_t r0, uint32_t r1, uint32_t r2, uint32_t r3) {
  asm volatile("stmatrix.sync.aligned.m8n8.x4.shared.b16 [%0], {%1,%2,%3,%4};" ::"r"(a), "r"(r0), "r"(r1), "r"(r2), "r"(r3) : "memory");
}
DEVI void ldsm4(uint32_t a, uint32_t& r0, uint32_t& r1, uint32_t& r2, uint32_t& r3) {
  asm volatile("ldmatrix.sync.aligned.m8n8.x4.shared.b16 {%0,%1,%2,%3}, [%4];" : "=r"(r0), "=r"(r1), "=r"(r2), "=r"(r3) : "r"(a) : "memory");
}
DEVI uint32_t pack2(float lo, float hi) { uint32_t r; asm("cvt.rn.bf16x2.f32 %0, %1, %2;" : "=r"(r) : "f"(hi), "f"(lo)); return r; }
DEVI float bf_lo(uint32_t v) { return __uint_as_float(v << 16); }
DEVI float bf_hi(uint32_t v) { return __uint_as_float(v & 0xffff0000u); }
DEVI float2 lds_f2(uint32_t a) { float2 v; asm volatile("ld.shared.v2.f32 {%0,%1}, [%2];" : "=f"(v.x), "=f"(v.y) : "r"(a)); return v; }
DEVI float4 lds_f4(uint32_t a) { float4 v; asm volatile("ld.shared.v4.f32 {%0,%1,%2,%3}, [%4];" : "=f"(v.x), "=f"(v.y), "=f"(v.z), "=f"(v.w) : "r"(a)); return v; }
DEVI uint4 lds_u4(uint32_t a) { uint4 v; asm volatile("ld.shared.v4.u32 {%0,%1,%2,%3}, [%4];" : "=r"(v.x), "=r"(v.y), "=r"(v.z), "=r"(v.w) : "r"(a)); return v; }
DEVI uint32_t lds_u32(uint32_t a) { uint32_t v; asm volatile("ld.shared.u32 %0, [%1];" : "=r"(v) : "r"(a)); return v; }
DEVI void sts_u32(uint32_t a, uint32_t v) { asm volatile("st.shared.u32 [%0], %1;" ::"r"(a), "r"(v) : "memory"); }
DEVI void sts_f2(uint32_t a, float x, float y) { asm volatile("st.shared.v2.f32 [%0], {%1,%2};" ::"r"(a), "f"(x), "f"(y) : "memory"); }
DEVI void sts_f4(uint32_t a, float x, float y, float z, float w) { asm volatile("st.shared.v4.f32 [%0], {%1,%2,%3,%4};" ::"r"(a), "f"(x), "f"(y), "f"(z), "f"(w) : "memory"); }
DEVI void sts_u4(uint32_t a, uint32_t x, uint32_t y, uint32_t z, uint32_t w) { asm volatile("st.shared.v4.u32 [%0], {%1,%2,%3,%4};" ::"r"(a), "r"(x), "r"(y), "r"(z), "r"(w) : "memory"); }
DEVI uint32_t ldg_u32(const void* p) { uint32_t v; asm volatile("ld.global.u32 %0, [%1];" : "=r"(v) : "l"(p)); return v; }
DEVI uint32_t ldg_nc_u32(const void* p) { uint32_t v; asm volatile("ld.global.nc.u32 %0, [%1];" : "=r"(v) : "l"(p)); return v; }
DEVI uint32_t ldg_nc_u16(const void* p) { uint32_t v; asm volatile("ld.global.nc.u16 %0, [%1];" : "=r"(v) : "l"(p)); return v; }
DEVI uint4 ldg_nc_u4(const void* p) { uint4 v; asm volatile("ld.global.nc.v4.u32 {%0,%1,%2,%3}, [%4];" : "=r"(v.x), "=r"(v.y), "=r"(v.z), "=r"(v.w) : "l"(p)); return v; }
DEVI uint2 ldg_nc_u2(const void* p) { uint2 v; asm volatile("ld.global.nc.v2.u32 {%0,%1}, [%2];" : "=r"(v.x), "=r"(v.y) : "l"(p)); return v; }
DEVI float2 ldg_cg_f2(const void* p) { float2 v; asm volatile("ld.global.cg.v2.f32 {%0,%1}, [%2];" : "=f"(v.x), "=f"(v.y) : "l"(p)); return v; }
DEVI float tanh_fast(float x) { float y; asm("tanh.approx.f32 %0, %1;" : "=f"(y) : "f"(x)); return y; }
DEVI float silu(float v) { float hv = 0.5f * v; return fmaf(hv, tanh_fast(hv), hv); }

template <int N> DEVI void zero(float (&a)[N]) {
#pragma unroll
  for (int i = 0; i < N; i++) a[i] = 0.f;
}
template <int N> DEVI void pin(float (&a)[N]) {
#pragma unroll
  for (int i = 0; i < N; i++) asm volatile("" : "+f"(a[i])::"memory");
}
DEVI void pin1(uint32_t& v) { asm volatile("" : "+r"(v)::"memory"); }
DEVI uint32_t hadd2(uint32_t a, uint32_t b) { uint32_t r; asm("add.rn.bf16x2 %0, %1, %2;" : "=r"(r) : "r"(a), "r"(b)); return r; }
DEVI uint32_t hfma2(uint32_t a, uint32_t b, uint32_t c) { uint32_t r; asm("fma.rn.bf16x2 %0, %1, %2, %3;" : "=r"(r) : "r"(a), "r"(b), "r"(c)); return r; }
DEVI void landed(uint32_t v) { asm volatile("{\n.reg .pred p;\nsetp.eq.u32 p, %0, 0x7fc17fc1;\n@p st.shared.u32 [%1], %0;\n}" ::"r"(v), "r"(EPO + 8) : "memory"); }
DEVI void staged(uint32_t bar, int lane) { fence_async_smem(); __syncwarp(); if (lane == 0) mbar_arrive(bar); }
DEVI float rsq(float x) { float y; asm("rsqrt.approx.ftz.f32 %0, %1;" : "=f"(y) : "f"(x)); return y; }
DEVI void acc8(float (&c)[8], const uint4& v) {
  c[0] += bf_lo(v.x); c[1] += bf_hi(v.x); c[2] += bf_lo(v.y); c[3] += bf_hi(v.y);
  c[4] += bf_lo(v.z); c[5] += bf_hi(v.z); c[6] += bf_lo(v.w); c[7] += bf_hi(v.w);
}
template<int TB,uint32_t HA,uint32_t HB> DEVI void wg_ss_80(float (&d)[40], uint32_t a, uint32_t b, int sd){
  asm volatile("{\n.reg .b64 da, db;\n.reg .pred p;\nsetp.ne.b32 p, %45, 0;\nmov.b64 da, {%40, %42};\nmov.b64 db, {%41, %43};\nwgmma.mma_async.sync.aligned.m64n80k16.f32.bf16.bf16 {%0,%1,%2,%3,%4,%5,%6,%7,%8,%9,%10,%11,%12,%13,%14,%15,%16,%17,%18,%19,%20,%21,%22,%23,%24,%25,%26,%27,%28,%29,%30,%31,%32,%33,%34,%35,%36,%37,%38,%39}, da, db, p, 1, 1, 0, %44;\n}\n"
    : "+f"(d[0]),"+f"(d[1]),"+f"(d[2]),"+f"(d[3]),"+f"(d[4]),"+f"(d[5]),"+f"(d[6]),"+f"(d[7]),"+f"(d[8]),"+f"(d[9]),"+f"(d[10]),"+f"(d[11]),"+f"(d[12]),"+f"(d[13]),"+f"(d[14]),"+f"(d[15]),"+f"(d[16]),"+f"(d[17]),"+f"(d[18]),"+f"(d[19]),"+f"(d[20]),"+f"(d[21]),"+f"(d[22]),"+f"(d[23]),"+f"(d[24]),"+f"(d[25]),"+f"(d[26]),"+f"(d[27]),"+f"(d[28]),"+f"(d[29]),"+f"(d[30]),"+f"(d[31]),"+f"(d[32]),"+f"(d[33]),"+f"(d[34]),"+f"(d[35]),"+f"(d[36]),"+f"(d[37]),"+f"(d[38]),"+f"(d[39])
    : "r"(a), "r"(b), "n"(HA), "n"(HB), "n"(TB), "r"(sd));
}
template<int TB,uint32_t HA,uint32_t HB> DEVI void wg_ss_160(float (&d)[80], uint32_t a, uint32_t b, int sd){
  asm volatile("{\n.reg .b64 da, db;\n.reg .pred p;\nsetp.ne.b32 p, %85, 0;\nmov.b64 da, {%80, %82};\nmov.b64 db, {%81, %83};\nwgmma.mma_async.sync.aligned.m64n160k16.f32.bf16.bf16 {%0,%1,%2,%3,%4,%5,%6,%7,%8,%9,%10,%11,%12,%13,%14,%15,%16,%17,%18,%19,%20,%21,%22,%23,%24,%25,%26,%27,%28,%29,%30,%31,%32,%33,%34,%35,%36,%37,%38,%39,%40,%41,%42,%43,%44,%45,%46,%47,%48,%49,%50,%51,%52,%53,%54,%55,%56,%57,%58,%59,%60,%61,%62,%63,%64,%65,%66,%67,%68,%69,%70,%71,%72,%73,%74,%75,%76,%77,%78,%79}, da, db, p, 1, 1, 0, %84;\n}\n"
    : "+f"(d[0]),"+f"(d[1]),"+f"(d[2]),"+f"(d[3]),"+f"(d[4]),"+f"(d[5]),"+f"(d[6]),"+f"(d[7]),"+f"(d[8]),"+f"(d[9]),"+f"(d[10]),"+f"(d[11]),"+f"(d[12]),"+f"(d[13]),"+f"(d[14]),"+f"(d[15]),"+f"(d[16]),"+f"(d[17]),"+f"(d[18]),"+f"(d[19]),"+f"(d[20]),"+f"(d[21]),"+f"(d[22]),"+f"(d[23]),"+f"(d[24]),"+f"(d[25]),"+f"(d[26]),"+f"(d[27]),"+f"(d[28]),"+f"(d[29]),"+f"(d[30]),"+f"(d[31]),"+f"(d[32]),"+f"(d[33]),"+f"(d[34]),"+f"(d[35]),"+f"(d[36]),"+f"(d[37]),"+f"(d[38]),"+f"(d[39]),"+f"(d[40]),"+f"(d[41]),"+f"(d[42]),"+f"(d[43]),"+f"(d[44]),"+f"(d[45]),"+f"(d[46]),"+f"(d[47]),"+f"(d[48]),"+f"(d[49]),"+f"(d[50]),"+f"(d[51]),"+f"(d[52]),"+f"(d[53]),"+f"(d[54]),"+f"(d[55]),"+f"(d[56]),"+f"(d[57]),"+f"(d[58]),"+f"(d[59]),"+f"(d[60]),"+f"(d[61]),"+f"(d[62]),"+f"(d[63]),"+f"(d[64]),"+f"(d[65]),"+f"(d[66]),"+f"(d[67]),"+f"(d[68]),"+f"(d[69]),"+f"(d[70]),"+f"(d[71]),"+f"(d[72]),"+f"(d[73]),"+f"(d[74]),"+f"(d[75]),"+f"(d[76]),"+f"(d[77]),"+f"(d[78]),"+f"(d[79])
    : "r"(a), "r"(b), "n"(HA), "n"(HB), "n"(TB), "r"(sd));
}
template<int TB,uint32_t HA,uint32_t HB> DEVI void wg_ss_192(float (&d)[96], uint32_t a, uint32_t b, int sd){
  asm volatile("{\n.reg .b64 da, db;\n.reg .pred p;\nsetp.ne.b32 p, %101, 0;\nmov.b64 da, {%96, %98};\nmov.b64 db, {%97, %99};\nwgmma.mma_async.sync.aligned.m64n192k16.f32.bf16.bf16 {%0,%1,%2,%3,%4,%5,%6,%7,%8,%9,%10,%11,%12,%13,%14,%15,%16,%17,%18,%19,%20,%21,%22,%23,%24,%25,%26,%27,%28,%29,%30,%31,%32,%33,%34,%35,%36,%37,%38,%39,%40,%41,%42,%43,%44,%45,%46,%47,%48,%49,%50,%51,%52,%53,%54,%55,%56,%57,%58,%59,%60,%61,%62,%63,%64,%65,%66,%67,%68,%69,%70,%71,%72,%73,%74,%75,%76,%77,%78,%79,%80,%81,%82,%83,%84,%85,%86,%87,%88,%89,%90,%91,%92,%93,%94,%95}, da, db, p, 1, 1, 0, %100;\n}\n"
    : "+f"(d[0]),"+f"(d[1]),"+f"(d[2]),"+f"(d[3]),"+f"(d[4]),"+f"(d[5]),"+f"(d[6]),"+f"(d[7]),"+f"(d[8]),"+f"(d[9]),"+f"(d[10]),"+f"(d[11]),"+f"(d[12]),"+f"(d[13]),"+f"(d[14]),"+f"(d[15]),"+f"(d[16]),"+f"(d[17]),"+f"(d[18]),"+f"(d[19]),"+f"(d[20]),"+f"(d[21]),"+f"(d[22]),"+f"(d[23]),"+f"(d[24]),"+f"(d[25]),"+f"(d[26]),"+f"(d[27]),"+f"(d[28]),"+f"(d[29]),"+f"(d[30]),"+f"(d[31]),"+f"(d[32]),"+f"(d[33]),"+f"(d[34]),"+f"(d[35]),"+f"(d[36]),"+f"(d[37]),"+f"(d[38]),"+f"(d[39]),"+f"(d[40]),"+f"(d[41]),"+f"(d[42]),"+f"(d[43]),"+f"(d[44]),"+f"(d[45]),"+f"(d[46]),"+f"(d[47]),"+f"(d[48]),"+f"(d[49]),"+f"(d[50]),"+f"(d[51]),"+f"(d[52]),"+f"(d[53]),"+f"(d[54]),"+f"(d[55]),"+f"(d[56]),"+f"(d[57]),"+f"(d[58]),"+f"(d[59]),"+f"(d[60]),"+f"(d[61]),"+f"(d[62]),"+f"(d[63]),"+f"(d[64]),"+f"(d[65]),"+f"(d[66]),"+f"(d[67]),"+f"(d[68]),"+f"(d[69]),"+f"(d[70]),"+f"(d[71]),"+f"(d[72]),"+f"(d[73]),"+f"(d[74]),"+f"(d[75]),"+f"(d[76]),"+f"(d[77]),"+f"(d[78]),"+f"(d[79]),"+f"(d[80]),"+f"(d[81]),"+f"(d[82]),"+f"(d[83]),"+f"(d[84]),"+f"(d[85]),"+f"(d[86]),"+f"(d[87]),"+f"(d[88]),"+f"(d[89]),"+f"(d[90]),"+f"(d[91]),"+f"(d[92]),"+f"(d[93]),"+f"(d[94]),"+f"(d[95])
    : "r"(a), "r"(b), "n"(HA), "n"(HB), "n"(TB), "r"(sd));
}
template<int SD,int TB,uint32_t HB> DEVI void wg_rs_32(float (&d)[16], uint32_t a0, uint32_t a1, uint32_t a2, uint32_t a3, uint32_t b){
  asm volatile("{\n.reg .b64 db;\nmov.b64 db, {%20, %21};\nwgmma.mma_async.sync.aligned.m64n32k16.f32.bf16.bf16 {%0,%1,%2,%3,%4,%5,%6,%7,%8,%9,%10,%11,%12,%13,%14,%15}, {%16,%17,%18,%19}, db, %22, 1, 1, %23;\n}\n"
    : "+f"(d[0]),"+f"(d[1]),"+f"(d[2]),"+f"(d[3]),"+f"(d[4]),"+f"(d[5]),"+f"(d[6]),"+f"(d[7]),"+f"(d[8]),"+f"(d[9]),"+f"(d[10]),"+f"(d[11]),"+f"(d[12]),"+f"(d[13]),"+f"(d[14]),"+f"(d[15])
    : "r"(a0),"r"(a1),"r"(a2),"r"(a3), "r"(b), "n"(HB), "n"(SD), "n"(TB));
}
template<int SD,int TB,uint32_t HB> DEVI void wg_rs_64(float (&d)[32], uint32_t a0, uint32_t a1, uint32_t a2, uint32_t a3, uint32_t b){
  asm volatile("{\n.reg .b64 db;\nmov.b64 db, {%36, %37};\nwgmma.mma_async.sync.aligned.m64n64k16.f32.bf16.bf16 {%0,%1,%2,%3,%4,%5,%6,%7,%8,%9,%10,%11,%12,%13,%14,%15,%16,%17,%18,%19,%20,%21,%22,%23,%24,%25,%26,%27,%28,%29,%30,%31}, {%32,%33,%34,%35}, db, %38, 1, 1, %39;\n}\n"
    : "+f"(d[0]),"+f"(d[1]),"+f"(d[2]),"+f"(d[3]),"+f"(d[4]),"+f"(d[5]),"+f"(d[6]),"+f"(d[7]),"+f"(d[8]),"+f"(d[9]),"+f"(d[10]),"+f"(d[11]),"+f"(d[12]),"+f"(d[13]),"+f"(d[14]),"+f"(d[15]),"+f"(d[16]),"+f"(d[17]),"+f"(d[18]),"+f"(d[19]),"+f"(d[20]),"+f"(d[21]),"+f"(d[22]),"+f"(d[23]),"+f"(d[24]),"+f"(d[25]),"+f"(d[26]),"+f"(d[27]),"+f"(d[28]),"+f"(d[29]),"+f"(d[30]),"+f"(d[31])
    : "r"(a0),"r"(a1),"r"(a2),"r"(a3), "r"(b), "n"(HB), "n"(SD), "n"(TB));
}
template<int SD,int TB,uint32_t HB> DEVI void wg_rs_128(float (&d)[64], uint32_t a0, uint32_t a1, uint32_t a2, uint32_t a3, uint32_t b){
  asm volatile("{\n.reg .b64 db;\nmov.b64 db, {%68, %69};\nwgmma.mma_async.sync.aligned.m64n128k16.f32.bf16.bf16 {%0,%1,%2,%3,%4,%5,%6,%7,%8,%9,%10,%11,%12,%13,%14,%15,%16,%17,%18,%19,%20,%21,%22,%23,%24,%25,%26,%27,%28,%29,%30,%31,%32,%33,%34,%35,%36,%37,%38,%39,%40,%41,%42,%43,%44,%45,%46,%47,%48,%49,%50,%51,%52,%53,%54,%55,%56,%57,%58,%59,%60,%61,%62,%63}, {%64,%65,%66,%67}, db, %70, 1, 1, %71;\n}\n"
    : "+f"(d[0]),"+f"(d[1]),"+f"(d[2]),"+f"(d[3]),"+f"(d[4]),"+f"(d[5]),"+f"(d[6]),"+f"(d[7]),"+f"(d[8]),"+f"(d[9]),"+f"(d[10]),"+f"(d[11]),"+f"(d[12]),"+f"(d[13]),"+f"(d[14]),"+f"(d[15]),"+f"(d[16]),"+f"(d[17]),"+f"(d[18]),"+f"(d[19]),"+f"(d[20]),"+f"(d[21]),"+f"(d[22]),"+f"(d[23]),"+f"(d[24]),"+f"(d[25]),"+f"(d[26]),"+f"(d[27]),"+f"(d[28]),"+f"(d[29]),"+f"(d[30]),"+f"(d[31]),"+f"(d[32]),"+f"(d[33]),"+f"(d[34]),"+f"(d[35]),"+f"(d[36]),"+f"(d[37]),"+f"(d[38]),"+f"(d[39]),"+f"(d[40]),"+f"(d[41]),"+f"(d[42]),"+f"(d[43]),"+f"(d[44]),"+f"(d[45]),"+f"(d[46]),"+f"(d[47]),"+f"(d[48]),"+f"(d[49]),"+f"(d[50]),"+f"(d[51]),"+f"(d[52]),"+f"(d[53]),"+f"(d[54]),"+f"(d[55]),"+f"(d[56]),"+f"(d[57]),"+f"(d[58]),"+f"(d[59]),"+f"(d[60]),"+f"(d[61]),"+f"(d[62]),"+f"(d[63])
    : "r"(a0),"r"(a1),"r"(a2),"r"(a3), "r"(b), "n"(HB), "n"(SD), "n"(TB));
}
template<int SD,int TB,uint32_t HB> DEVI void wg_rs_160(float (&d)[80], uint32_t a0, uint32_t a1, uint32_t a2, uint32_t a3, uint32_t b){
  asm volatile("{\n.reg .b64 db;\nmov.b64 db, {%84, %85};\nwgmma.mma_async.sync.aligned.m64n160k16.f32.bf16.bf16 {%0,%1,%2,%3,%4,%5,%6,%7,%8,%9,%10,%11,%12,%13,%14,%15,%16,%17,%18,%19,%20,%21,%22,%23,%24,%25,%26,%27,%28,%29,%30,%31,%32,%33,%34,%35,%36,%37,%38,%39,%40,%41,%42,%43,%44,%45,%46,%47,%48,%49,%50,%51,%52,%53,%54,%55,%56,%57,%58,%59,%60,%61,%62,%63,%64,%65,%66,%67,%68,%69,%70,%71,%72,%73,%74,%75,%76,%77,%78,%79}, {%80,%81,%82,%83}, db, %86, 1, 1, %87;\n}\n"
    : "+f"(d[0]),"+f"(d[1]),"+f"(d[2]),"+f"(d[3]),"+f"(d[4]),"+f"(d[5]),"+f"(d[6]),"+f"(d[7]),"+f"(d[8]),"+f"(d[9]),"+f"(d[10]),"+f"(d[11]),"+f"(d[12]),"+f"(d[13]),"+f"(d[14]),"+f"(d[15]),"+f"(d[16]),"+f"(d[17]),"+f"(d[18]),"+f"(d[19]),"+f"(d[20]),"+f"(d[21]),"+f"(d[22]),"+f"(d[23]),"+f"(d[24]),"+f"(d[25]),"+f"(d[26]),"+f"(d[27]),"+f"(d[28]),"+f"(d[29]),"+f"(d[30]),"+f"(d[31]),"+f"(d[32]),"+f"(d[33]),"+f"(d[34]),"+f"(d[35]),"+f"(d[36]),"+f"(d[37]),"+f"(d[38]),"+f"(d[39]),"+f"(d[40]),"+f"(d[41]),"+f"(d[42]),"+f"(d[43]),"+f"(d[44]),"+f"(d[45]),"+f"(d[46]),"+f"(d[47]),"+f"(d[48]),"+f"(d[49]),"+f"(d[50]),"+f"(d[51]),"+f"(d[52]),"+f"(d[53]),"+f"(d[54]),"+f"(d[55]),"+f"(d[56]),"+f"(d[57]),"+f"(d[58]),"+f"(d[59]),"+f"(d[60]),"+f"(d[61]),"+f"(d[62]),"+f"(d[63]),"+f"(d[64]),"+f"(d[65]),"+f"(d[66]),"+f"(d[67]),"+f"(d[68]),"+f"(d[69]),"+f"(d[70]),"+f"(d[71]),"+f"(d[72]),"+f"(d[73]),"+f"(d[74]),"+f"(d[75]),"+f"(d[76]),"+f"(d[77]),"+f"(d[78]),"+f"(d[79])
    : "r"(a0),"r"(a1),"r"(a2),"r"(a3), "r"(b), "n"(HB), "n"(SD), "n"(TB));
}

#define STAMP(i)
#define STAMPW(i)
#define GSTAMP(i)

DEVI uint32_t sw64(uint32_t row, uint32_t c) { return row * 64 + ((c ^ ((row >> 1) & 3)) << 4); }
DEVI uint32_t sw128(uint32_t row, uint32_t c) { return row * 128 + ((c ^ (row & 7)) << 4); }

DEVI float gelu_s(float t, float k0, float k1, float hr) {
  const float h = t * hr;
  return fmaf(h, tanh_fast(t * fmaf(t * t, k1, k0)), h);
}
struct GeluK { float mu0, mu1, a0, a1, ah, b0, b1, bh; };
DEVI GeluK gelu_k(float mu0, float mu1, float rs0, float rs1) {
  return GeluK{mu0, mu1, 0.7978845608f * rs0, 0.0356774081f * rs0 * rs0 * rs0, 0.5f * rs0, 0.7978845608f * rs1, 0.0356774081f * rs1 * rs1 * rs1, 0.5f * rs1};
}
DEVI void gelu_unit(const float* a, const GeluK& k, float2 c, float2 d, uint32_t dst) {
  stsm4(dst, pack2(gelu_s(fmaf(-k.mu0, c.x, a[0]), k.a0, k.a1, k.ah), gelu_s(fmaf(-k.mu0, c.y, a[1]), k.a0, k.a1, k.ah)),
        pack2(gelu_s(fmaf(-k.mu1, c.x, a[2]), k.b0, k.b1, k.bh), gelu_s(fmaf(-k.mu1, c.y, a[3]), k.b0, k.b1, k.bh)),
        pack2(gelu_s(fmaf(-k.mu0, d.x, a[4]), k.a0, k.a1, k.ah), gelu_s(fmaf(-k.mu0, d.y, a[5]), k.a0, k.a1, k.ah)),
        pack2(gelu_s(fmaf(-k.mu1, d.x, a[6]), k.b0, k.b1, k.bh), gelu_s(fmaf(-k.mu1, d.y, a[7]), k.b0, k.b1, k.bh)));
}

DEVI void d_frags(uint32_t (&D)[8], int c0, int cs, int lane) {
#pragma unroll
  for (int i = 0; i < 4; i++) {
    const int v = c0 + cs * (8 * i + 2 * (lane & 3)) + 1024;
    const float a0 = (float)((v & 2047) - 1024) * 0.0030679615757712823f, a1 = (float)(((v + cs) & 2047) - 1024) * 0.0030679615757712823f;
    D[2 * i] = pack2(__cosf(a0), __cosf(a1)); D[2 * i + 1] = pack2(__sinf(a0), __sinf(a1));
  }
}

DEVI void fold(int b, int j, uint32_t row128, uint32_t sx, float mu0, float mu1, int odd) {
  const uint32_t dst = SM + (j ? j - 1 : 5) * SLOT + row128;
  const uint32_t oth = (j < 2 ? SM + 4 * SLOT + 8192 + j * 8192 : j == 2 ? FB + 16384 : j == 3 ? FB : SM + 4 * SLOT) + row128;
  const bool lo = g1_chunk(b, j) < 5;
  const uint32_t xa = lo ? oth : dst, xb = lo ? dst : oth;
  const float km = odd ? 0.f : -2.f;
  const uint32_t np0 = pack2(mu0 * km, mu0 * km), np1 = pack2(mu1 * km, mu1 * km), sg = odd ? 0xbf80bf80u : 0x3f803f80u;
  uint32_t u[16], v[16];
#pragma unroll
  for (int kk = 0; kk < 4; kk++) {
    ldsm4(xa + (sx ^ (kk << 5)), u[4 * kk], u[4 * kk + 1], u[4 * kk + 2], u[4 * kk + 3]);
    ldsm4(xb + (sx ^ (kk << 5)), v[4 * kk], v[4 * kk + 1], v[4 * kk + 2], v[4 * kk + 3]);
  }
#pragma unroll
  for (int kk = 0; kk < 4; kk++)
    stsm4(dst + (sx ^ (kk << 5)), hfma2(v[4 * kk], sg, hadd2(u[4 * kk], np0)), hfma2(v[4 * kk + 1], sg, hadd2(u[4 * kk + 1], np1)),
          hfma2(v[4 * kk + 2], sg, hadd2(u[4 * kk + 2], np0)), hfma2(v[4 * kk + 3], sg, hadd2(u[4 * kk + 3], np1)));
}

DEVI void mlp_role(const Params& P, int b, int q, int wg, int w, uint32_t t_start) {
  const int tid = threadIdx.x, lane = tid & 31;
  const int odd = q & 1;
  const int r0 = 16 * w + (lane >> 2);
  const int srow = 16 * w + (lane & 7) + ((lane >> 3) & 1) * 8;
  const int schk = lane >> 4;
  uint32_t phM = 0;
  uint32_t s = 0, sp = 0;
  const bool rel = (tid & 127) == 0;
#define STAGE_WAIT() mbar_wait(B_FM + s * 8, (phM >> s) & 1); phM ^= 1u << s; const uint32_t so = s * SL16; wg_fence();
#define STAGE_NEXT() wg_commit(); wg_wait<1>(); if (rel && it > 0) mbar_arrive(B_EM + sp * 8); sp = s; s = s == NST - 1 ? 0 : s + 1;
#define STAGE_END() wg_wait<0>(); if (rel) mbar_arrive(B_EM + sp * 8);

  const int ga = 2 * wg + odd, gs = odd ? 0 : 4;
  const uint32_t oA = sw64(srow, schk), oB = sw64(srow, 2 + schk);
  constexpr uint32_t dA = dlo(SM, 16);
  const uint32_t dBlo = dlo(SM + 8192, 16384) + wg * (dlo(8192, 0) - dlo(0, 8192 - 32));
  const uint32_t dBhi = dBlo + dlo(4096, 0) - dlo(0, 4096 - 64);
  float mu0, mu1;
  const uint32_t o128 = srow * 128, x128 = ((srow & 7) ^ schk) << 4;
  uint32_t wf[20], nr = 0, ni = 0;
  const int k1 = 2 * b + (q >> 1), k2 = 8 * w + (lane >> 2);
  const bool nyq = !odd && !wg && (lane & 3) == 0;
  uint32_t xf[20], yv[20];
#pragma unroll
  for (int i = 0; i < 20; i++) xf[i] = 0;
  {
    float acc[40];
    const uint32_t dB1 = dBlo + dlo(4096, FB - SM - 28672);
    STAMPW(80);
#pragma unroll 1
    for (int it = 0; it < 10; it++) {
      mbar_wait(B_FM + s * 8, (phM >> s) & 1); phM ^= 1u << s;
      const uint32_t so = s * SL16;
      if (it == 0) STAMPW(82);
      const int ck = g1_chunk(b, it);
      if (ck == q + 5 * wg) {
#pragma unroll
        for (int j = 0; j < 4; j++) ldsm4(SM + s * SLOT + o128 + (x128 ^ (j << 5)), xf[4 * j], xf[4 * j + 1], xf[4 * j + 2], xf[4 * j + 3]);
      }
      if (ck == 4 + 5 * wg) { ldsm4(SM + s * SLOT + o128 + (x128 ^ (q << 5)), xf[16], xf[17], xf[18], xf[19]); }
      const uint32_t dh = dB1 + so - s * dlo(0, SLOT - 4096);
      wg_fence();
#pragma unroll
      for (int kk = 0; kk < 4; kk++) wg_ss_80<1, H128, H128>(acc, dA + so + kk * 2, (kk < 2 ? dBlo + so : dh) + (kk & 1) * 128, kk ? 1 : it);
      STAGE_NEXT();
      landed(xf[0] ^ xf[4] ^ xf[8] ^ xf[12] ^ xf[16]);
    }
    wg_fence();
    STAGE_END();
    STAMPW(12); GSTAMP(16);
    const int carry = (b + (q & 2 ? 2 : 1) * (odd ? -1 : 1)) >> 5;
    const int drow = (srow + carry) & 63;
    const uint32_t dA_ = STG + sw64(drow, schk), dB_ = STG + sw64(drow, 2 + schk);
    nb_sync(NB_STATS, 416);
    const float4 s0 = lds_f4(ROW + r0 * 16), s1 = lds_f4(ROW + 128 + r0 * 16);
    mu0 = s0.x; mu1 = s1.x;
    const float rs0 = (r0 + carry < 0) ? 0.f : s0.z, rs1 = (r0 + 8 + carry >= 64) ? 0.f : s1.z;
    pin(acc);
    STAMPW(1);
    const GeluK gk = gelu_k(mu0, mu1, rs0, rs1);
    float2 cs[10];
#pragma unroll
    for (int j = 0; j < 10; j++) cs[j] = lds_f2(CS1 + (lane & 3) * 8 + (j < 8 ? ga * 128 + j * 32 : gs * 128 + wg * 64 + (j - 8) * 32));
#pragma unroll
    for (int j = 0; j < 5; j++) {
      gelu_unit(&acc[8 * j], gk, cs[2 * j], cs[2 * j + 1], j < 4 ? (ga + (j >> 1)) * 4096 + ((j & 1) ? dB_ : dA_) : gs * 4096 + (wg ? dB_ : dA_));
    }
    staged(B_H2, lane);
    STAMPW(2);
  }
  if (nyq) { const int o = (k1 + 64 * k2) * 321 + 320; nr = ldg_nc_u16(P.pwr + o); ni = ldg_nc_u16(P.pwi + o); }
  uint32_t E[16];
  {
    const int u = 32 * wg + k2;
    const float ng = (u & 1) ? -1.f : 1.f;
#pragma unroll
    for (int i = 0; i < 4; i++) {
      const int a = 8 * i + 2 * (lane & 3), v = u * a + 32;
      const float a0 = (float)((v & 63) - 32) * 0.09817477042468103f, a1 = (float)(((v + u) & 63) - 32) * 0.09817477042468103f;
      const float c0 = __cosf(a0), c1 = __cosf(a1), s0 = __sinf(a0), s1 = __sinf(a1);
      const float r0_ = __uint_as_float(lds_u32(ROW + 4 + a * 16)), r1_ = __uint_as_float(lds_u32(ROW + 20 + a * 16));
      const float r2_ = ng * __uint_as_float(lds_u32(ROW + 516 + a * 16)), r3_ = ng * __uint_as_float(lds_u32(ROW + 532 + a * 16));
      E[2 * i] = pack2(c0 * r0_, c1 * r1_); E[2 * i + 1] = pack2(s0 * r0_, s1 * r1_);
      E[8 + 2 * i] = pack2(c0 * r2_, c1 * r3_); E[9 + 2 * i] = pack2(s0 * r2_, s1 * r3_);
    }
    landed(E[0] ^ E[7] ^ E[9] ^ E[15]);
  }
    {
      const uint32_t a = STG + k2 * 352 + ((((k1 & 15) + wg) >> 1) + (lane & 3)) * 4, se = ((k1 ^ wg) & 1) ? 0x7632 : 0x5410;
      mbar_wait(B_CS, 0);
      STAMPW(77);
#pragma unroll
      for (int j = 0; j < 20; j++) {
        const uint32_t ad = a + j * 16 + (j < 16 ? wg * 64 : wg * -256);
        wf[j] = __byte_perm(lds_u32(ad), lds_u32(ad + 11264), se);
      }
      if (nyq) wf[0] = pack2(0.5f * bf_lo(nr), 0.5f * bf_lo(ni));
      landed(wf[19] ^ wf[18] ^ wf[15]);
      STAMPW(36);
    }
  {
    float acc[80];
    nb_sync(NB_F1, 384);
    wg_fence();
    wg_rs_160<0, 1, H128>(acc, E[0], E[1], E[2], E[3], dlo(FB, 8192));
    wg_rs_160<1, 1, H128>(acc, E[4], E[5], E[6], E[7], dlo(FB, 8192) + 128);
    wg_rs_160<1, 1, H128>(acc, E[8], E[9], E[10], E[11], dlo(FB, 8192) + 256);
    wg_rs_160<1, 1, H128>(acc, E[12], E[13], E[14], E[15], dlo(FB, 8192) + 384);
    wg_commit(); wg_wait<0>();
    pin(acc);
    uint32_t o[20];
#pragma unroll
    for (int i = 0; i < 20; i++) o[i] = pack2(acc[4 * i] + acc[4 * i + 3], acc[4 * i + 1] - acc[4 * i + 2]);
    nb_sync(NB_MLP, 256);
    const uint32_t vb = FB + (32 * wg + 8 * w + (lane & 7)) * 128, vx = ((lane & 7) ^ (lane >> 3)) << 4;
#pragma unroll
    for (int j = 0; j < 5; j++) stsm4(vb + (j >> 1) * 8192 + (vx ^ ((j & 1) << 6)), o[4 * j], o[4 * j + 1], o[4 * j + 2], o[4 * j + 3]);
    fence_async_smem();
    nb_arrive(NB_T2, 288);
    STAMPW(35);
  }
  s = 16 % NST;
  {
    float acc[40];
    const float ra = __uint_as_float(lds_u32(ROW + 4 + r0 * 16)), rb = __uint_as_float(lds_u32(ROW + 132 + r0 * 16));
#pragma unroll 1
    for (int it = 0; it < 10; it++) {
      STAGE_WAIT();
      if (it == 0) { STAMPW(3); GSTAMP(17); }
#pragma unroll
      for (int kk = 0; kk < 4; kk++) wg_ss_80<1, H64, H128>(acc, dA + so + (kk >> 1) * 256 + (kk & 1) * 2, (kk < 2 ? dBlo : dBhi) + so + (kk & 1) * 128, kk ? 1 : it);
      STAGE_NEXT();
    }
    STAGE_END();
    pin(acc);
    STAMPW(4); GSTAMP(18);
    const float n0 = -mu0 * ra, n1 = -mu1 * rb;
#pragma unroll
    for (int j = 0; j < 5; j++) {
#pragma unroll
      for (int f = 4 * j; f < 4 * j + 4; f++) {
        const float r_ = (f & 1) ? rb : ra, n_ = (f & 1) ? n1 : n0;
        yv[f] = pack2(fmaf(bf_lo(xf[f]), r_, n_) + acc[2 * f], fmaf(bf_hi(xf[f]), r_, n_) + acc[2 * f + 1]);
      }
      stsm4(STG + j * 4096 + (wg ? oB : oA), yv[4 * j], yv[4 * j + 1], yv[4 * j + 2], yv[4 * j + 3]);
    }
    staged(B_H2, lane);
    STAMPW(5);
    float s0 = 0.f, s1 = 0.f, v0 = 0.f, v1 = 0.f;
#pragma unroll
    for (int j = 0; j < 10; j++) {
      pin1(yv[2 * j]); pin1(yv[2 * j + 1]);
      const float a0 = bf_lo(yv[2 * j]), a1 = bf_hi(yv[2 * j]), a2 = bf_lo(yv[2 * j + 1]), a3 = bf_hi(yv[2 * j + 1]);
      s0 += a0 + a1; s1 += a2 + a3; v0 = fmaf(a0, a0, fmaf(a1, a1, v0)); v1 = fmaf(a2, a2, fmaf(a3, a3, v1));
    }
#pragma unroll
    for (int o = 1; o < 4; o <<= 1) {
      s0 += __shfl_xor_sync(~0u, s0, o); s1 += __shfl_xor_sync(~0u, s1, o); v0 += __shfl_xor_sync(~0u, v0, o); v1 += __shfl_xor_sync(~0u, v1, o);
    }
    if ((lane & 3) == 0) { sts_f2(ST1 + wg * 512 + r0 * 8, s0, v0); sts_f2(ST1 + 64 + wg * 512 + r0 * 8, s1, v1); }
    fence_async_smem();
    nb_arrive(NB_RDY, 288);
  }
  {
    const uint32_t dV = dlo(FB, 4096) + wg * 768;
    const uint32_t vb = FB + wg * 12288 + (8 * w + (lane & 7)) * 128, vx = ((lane & 7) ^ (lane >> 3)) << 4;
    mbar_wait(B_FFT, 0);
    STAMPW(38);
#pragma unroll
    for (int ps = 0; ps < 2; ps++) {
      float ac0[64], ac1[16];
      const uint4 d0 = lds_u4((ps ? DFR + 2048 : DF0) + (tid & 127) * 16), d1 = lds_u4(DFR + ps * 4096 + (tid & 127) * 16);
      const uint32_t D[8] = {d0.x, d0.y, d0.z, d0.w, d1.x, d1.y, d1.z, d1.w};
      wg_fence();
      wg_rs_128<0, 1, H128>(ac0, D[0], D[1], D[2], D[3], dV);
      wg_rs_128<1, 1, H128>(ac0, D[4], D[5], D[6], D[7], dV + 128);
      wg_rs_32<0, 1, H128>(ac1, D[0], D[1], D[2], D[3], dlo(FB + 8192, 4096) + wg * 4);
      wg_rs_32<1, 1, H128>(ac1, D[4], D[5], D[6], D[7], dlo(FB + 8192, 4096) + 128 + wg * 4);
      wg_commit(); wg_wait<0>();
      pin(ac0); pin(ac1);
      nb_sync(NB_WG0 + wg, 128);
#pragma unroll
      for (int j = 0; j < 5; j++) {
        uint32_t o[4];
#pragma unroll
        for (int u = 0; u < 4; u++) {
          const float* a = j < 4 ? &ac0[16 * j + 4 * u] : &ac1[4 * u];
          if (ps == 0) {
            const float xr = a[0] + a[3], xi = a[1] - a[2], wr = bf_lo(wf[4 * j + u]), wi = bf_hi(wf[4 * j + u]);
            o[u] = pack2(xr * wr - xi * wi, xr * wi + xi * wr);
          } else o[u] = pack2(a[0] - a[3], a[1] + a[2]);
        }
        stsm4(j < 4 ? vb + (j >> 1) * 4096 + (vx ^ ((j & 1) << 6)) : vb + 8192 - wg * 12288 + (vx ^ (wg << 6)), o[0], o[1], o[2], o[3]);
      }
      fence_async_smem();
      if (ps == 0) nb_sync(NB_WG0 + wg, 128);
    }
    STAMPW(39);
  }
  {
    float ac3[96];
    const uint32_t dA3 = dA + wg * 256;
    constexpr uint32_t dB = dlo(SM + 8192, 2048);
    mbar_wait(B_FM + s * 8, (phM >> s) & 1);
    nb_arrive(NB_T2, 288);
    STAMPW(6); GSTAMP(19);
    float m0, m1, rs0, rs1;
    float2 pa0, pa1, pb0, pb1;
    pa0.x = pa0.y = 0.f; pa1 = pb0 = pb1 = pa0;
#pragma unroll 1
    for (int it = 0; it < 20; it++) {
      STAGE_WAIT();
      wg_ss_192<1, H64, H128>(ac3, dA3 + so, dB + so, it);
      wg_ss_192<1, H64, H128>(ac3, dA3 + so + 2, dB + so + 384, 1);
      STAGE_NEXT();
      if (it == 18) {
        mbar_wait(B_ROW, 1);
        const uint32_t sa = STP + wg * 4096 + (lane & 3) * 1024 + r0 * 8;
        pa0 = lds_f2(sa); pa1 = lds_f2(sa + 512); pb0 = lds_f2(sa + 64); pb1 = lds_f2(sa + 576);
      }
    }
    m0 = pa0.x + pa1.x; m1 = pb0.x + pb1.x;
    float v0 = pa0.y + pa1.y, v1 = pb0.y + pb1.y;
#pragma unroll
    for (int o = 1; o < 4; o <<= 1) {
      m0 += __shfl_xor_sync(~0u, m0, o); m1 += __shfl_xor_sync(~0u, m1, o); v0 += __shfl_xor_sync(~0u, v0, o); v1 += __shfl_xor_sync(~0u, v1, o);
    }
    m0 *= 1.f / 640.f; m1 *= 1.f / 640.f;
    rs0 = rsq(fmaxf(fmaf(-m0, m0, v0 * (1.f / 640.f)), 0.f) + 1e-5f); rs1 = rsq(fmaxf(fmaf(-m1, m1, v1 * (1.f / 640.f)), 0.f) + 1e-5f);
    const GeluK gk = gelu_k(m0, m1, rs0, rs1);
    landed(__float_as_uint(gk.a1) ^ __float_as_uint(gk.b1));
    STAGE_END();
    STAMPW(7); GSTAMP(20);
    pin(ac3);
#pragma unroll 1
    for (int r = 0; r < 2; r++) {
      float2 cs[12];
#pragma unroll
      for (int j = 0; j < 4; j++) cs[j] = lds_f2(CS3 + r * 384 + j * 32 + (lane & 3) * 8);
#pragma unroll
      for (int h = 0; h < 3; h++) {
        const uint32_t buf = STG + r * 24576 + h * 8192 + wg * 4096;
        if (h < 2) {
#pragma unroll
          for (int j = 4 * h + 4; j < 4 * h + 8; j++) cs[j] = lds_f2(CS3 + r * 384 + j * 32 + (lane & 3) * 8);
        }
        if (h == 2) mbar_wait(B_H2, 0);
        gelu_unit(&ac3[16 * h], gk, cs[4 * h], cs[4 * h + 1], buf + oA);
        gelu_unit(&ac3[16 * h + 8], gk, cs[4 * h + 2], cs[4 * h + 3], buf + oB);
        staged(B_H2 + (3 * r + h) * 8, lane);
      }
      if (r) break;
#pragma unroll
      for (int i = 0; i < 48; i++) ac3[i] = ac3[i + 48];
      mbar_wait(B_YD, 0);
    }
    STAMPW(8);
  }
  {
  float acc[40];
#pragma unroll 1
  for (int it = 0; it < 24; it++) {
    STAGE_WAIT();
    if (it == 0) { STAMPW(9); GSTAMP(21); }
#pragma unroll
    for (int kk = 0; kk < 4; kk++) wg_ss_80<1, H64, H128>(acc, dA + so + (kk >> 1) * 256 + (kk & 1) * 2, (kk < 2 ? dBlo : dBhi) + so + (kk & 1) * 128, kk ? 1 : it);
    STAGE_NEXT();
  }
  STAGE_END();
  pin(acc);
#pragma unroll
  for (int i = 0; i < 20; i++) { asm volatile("mov.b32 %0, %0;" : "+r"(xf[i])); asm volatile("mov.b32 %0, %0;" : "+r"(yv[i])); }
  STAMPW(10); GSTAMP(22);
#pragma unroll
  for (int f = 0; f < 20; f++) { acc[2 * f] = silu(bf_lo(yv[f]) + acc[2 * f]); acc[2 * f + 1] = silu(bf_hi(yv[f]) + acc[2 * f + 1]); }
  {
    float z = 0.f;
#pragma unroll
    for (int f = 0; f < 40; f += 2) z = fmaf(acc[f], acc[f + 1], z);
    landed(__float_as_uint(z));
  }
  STAMPW(13);
  nb_sync(NB_S, 384);
  STAMPW(14);
#pragma unroll
  for (int j = 0; j < 5; j++) {
    uint32_t sv[4], o[4];
    const uint32_t ot = j < 4 ? wg * 8192 + o128 + (x128 ^ (j << 5)) : 16384 + wg * 2048 + srow * 32 + ((schk ^ ((srow >> 2) & 1)) << 4);
    ldsm4(FB + (j < 4 ? ot : 16384 + o128 + (x128 ^ (wg << 5))), sv[0], sv[1], sv[2], sv[3]);
#pragma unroll
    for (int u = 0; u < 4; u++) {
      const int f = 4 * j + u;
      o[u] = pack2(fmaf(bf_lo(sv[u]), acc[2 * f], bf_lo(xf[f])), fmaf(bf_hi(sv[u]), acc[2 * f + 1], bf_hi(xf[f])));
    }
    stsm4(STG + ot, o[0], o[1], o[2], o[3]);
  }
  fence_async_smem();
  nb_arrive(NB_RDY, 288);
  STAMPW(11); GSTAMP(23);
  }
#undef STAGE_WAIT
#undef STAGE_NEXT
#undef STAGE_END
}

DEVI void e_frags(uint32_t (&Cf)[16], uint32_t (&Sf)[16], int r0, int lane) {
  const float sc = 2.f / (2048.f * 640.f);
  const uint32_t sneg = 0x80008000u;
#pragma unroll
  for (int i = 0; i < 4; i++) {
    const int row = r0 + 8 * (i & 1), i0 = row * (8 * (i >> 1) + 2 * (lane & 3)) + 32;
    const float a0 = (float)((i0 & 63) - 32) * 0.09817477042468103f, a1 = (float)(((i0 + row) & 63) - 32) * 0.09817477042468103f;
    Cf[i] = pack2(sc * __cosf(a0), sc * __cosf(a1)); Sf[i] = pack2(sc * __sinf(a0), sc * __sinf(a1));
  }
  const bool sw = r0 & 1;
  const uint32_t N = 0x80008000u, m1 = sw ? N : 0u;
  const uint32_t nc = ((r0 + 1) & 2) ? N : 0u, ns = ((r0 & 2) ? N : 0u) ^ sneg;
#pragma unroll
  for (int i = 0; i < 4; i++) {
    Cf[4 + i] = (sw ? Sf[i] : Cf[i]) ^ nc; Sf[4 + i] = (sw ? Cf[i] : Sf[i]) ^ ns;
    Sf[i] ^= sneg;
    Cf[8 + i] = Cf[i] ^ m1; Sf[8 + i] = Sf[i] ^ m1; Cf[12 + i] = Cf[4 + i] ^ m1; Sf[12 + i] = Sf[4 + i] ^ m1;
  }
}
DEVI void s_step(const uint32_t (&Cf)[16], const uint32_t (&Sf)[16], int na, uint32_t sbase, uint32_t sx) {
#pragma unroll 1
  for (int i = 0; i < na; i++) {
    const uint32_t dU = dlo(FB, 8192) + i * 512;
    float p[32], r[32];
    wg_fence();
    wg_rs_64<0, 1, H128>(p, Cf[0], Cf[1], Cf[2], Cf[3], dU);
    wg_rs_64<0, 1, H128>(r, Sf[0], Sf[1], Sf[2], Sf[3], dU);
#pragma unroll
    for (int kk = 1; kk < 4; kk++) {
      wg_rs_64<1, 1, H128>(p, Cf[4 * kk], Cf[4 * kk + 1], Cf[4 * kk + 2], Cf[4 * kk + 3], dU + kk * 128);
      wg_rs_64<1, 1, H128>(r, Sf[4 * kk], Sf[4 * kk + 1], Sf[4 * kk + 2], Sf[4 * kk + 3], dU + kk * 128);
    }
    wg_commit(); wg_wait<0>();
    pin(p); pin(r);
    nb_sync(NB_WG2, 128);
#pragma unroll
    for (int j = 0; j < 4; j++) {
      uint32_t o[4];
#pragma unroll
      for (int u = 0; u < 4; u++) { const int f = 2 * (4 * j + u); o[u] = pack2(p[f] + r[f + 1], p[f + 1] - r[f]); }
      stsm4(sbase + i * 8192 + (sx ^ (j << 5)), o[0], o[1], o[2], o[3]);
    }
  }
  fence_async_smem();
  nb_arrive(NB_DMA, 160);
}

DEVI void fft_role(const Params& P, int slot, int w, uint32_t t_start) {
  const int b = slot >> 2, q = slot & 3, odd = q & 1;
  const int t = threadIdx.x & 127, lane = t & 31;
  const int r0 = 16 * w + (lane >> 2);
  const int srow = 16 * w + (lane & 7) + ((lane >> 3) & 1) * 8;
  const uint32_t sbase = FB + srow * 128, sx = ((srow & 7) ^ (lane >> 4)) << 4;

  uint32_t ep;
  {
    const __nv_bfloat16* p = P.px + (32 * (16 * q + (t >> 3)) + b) * 640 + 8 * (t & 7);
    uint4 ev[10];
    STAMPW(50);
    const int c0 = g1_chunk(b, 0);
    p += c0 * 64;
#pragma unroll
    for (int i = 0; i < 10; i++) { if (i + c0 == 10) p -= 640; ev[i] = ldg_nc_u4(p + i * 64); }
    {
      const int pc = min(t >> 3, 9), it = pc >= 5, rg = t & 7;
      const int cc = 5 * (b & 3) + pc - 5 * it;
      const uint32_t b0 = (cc < 16 ? SM + it * SLOT + 8192 + (cc >> 3) * 8192 : SM + it * SLOT + 24576) + sw128(rg, cc & 7);
      const uint32_t b1 = cc < 16 ? b0 + 4096 : FB + it * 4096 + sw128(rg, cc & 7);
      float c8[8];
      zero(c8);
      if (w < 3) {
        mbar_wait(B_FM + (w ? 8 : 0), 0);
        if (w == 1) mbar_wait(B_FM, 0);
#pragma unroll 1
        for (int hf = 0; hf < 2; hf++) {
#pragma unroll
          for (int i = 0; i < 4; i++) acc8(c8, lds_u4((hf ? b1 : b0) + i * 1024));
        }
        landed(__float_as_uint(c8[0]));
        if (lane == 0) mbar_arrive(B_CSR);
      }
#pragma unroll
      for (int i = 0; i < 4; i++) { const bool up = lane & 4; const float o = __shfl_xor_sync(~0u, up ? c8[i] : c8[i + 4], 4); c8[i] = (up ? c8[i + 4] : c8[i]) + o; }
#pragma unroll
      for (int i = 0; i < 2; i++) { const bool up = lane & 2; const float o = __shfl_xor_sync(~0u, up ? c8[i] : c8[i + 2], 2); c8[i] = (up ? c8[i + 2] : c8[i]) + o; }
      { const bool up = lane & 1; const float o = __shfl_xor_sync(~0u, up ? c8[0] : c8[1], 1); c8[0] = (up ? c8[1] : c8[0]) + o; }
      const int col = 160 * q + 8 * (odd ? (cc >= 16 ? cc - 16 : cc + 4) : cc) + rg;
      mbar_wait(B_EP, 0);
      ep = lds_u32(EPO);
      if (t < ((b & 12) == 12 ? 80 : 40))
        asm volatile("st.relaxed.gpu.global.u32 [%0], %1;" ::"l"(SC(cs1, (g1_chunk(b, it) * 640 + col) * 4)), "r"((__float_as_uint(c8[0]) & ~1u) | (ep & 1)) : "memory");
      __syncwarp();
    }
    STAMPW(32);
    float c[4], d[4];
    zero(c); zero(d);
#pragma unroll 1
    for (int hf = 0; hf < 2; hf++) {
#pragma unroll
      for (int i = 0; i < 5; i++) {
        const uint32_t e[4] = {ev[i].x, ev[i].y, ev[i].z, ev[i].w};
#pragma unroll
        for (int k = 0; k < 4; k++) {
          const float lo = bf_lo(e[k]), hi = bf_hi(e[k]);
          c[k] += lo + hi; d[k] = fmaf(lo, lo, fmaf(hi, hi, d[k]));
        }
        ev[i] = ev[i + 5];
      }
    }
    float a = (c[0] + c[1]) + (c[2] + c[3]), g = (d[0] + d[1]) + (d[2] + d[3]);
#pragma unroll
    for (int o = 1; o < 8; o <<= 1) { a += __shfl_xor_sync(~0u, a, o); g += __shfl_xor_sync(~0u, g, o); }
    const float m = a * (1.f / 640.f), var = fmaxf(fmaf(-m, m, g * (1.f / 640.f)), 0.f), r1 = rsq(var + 1e-5f);
    if ((t & 7) == 0)
      asm volatile("st.relaxed.gpu.global.v4.f32 [%0], {%1,%2,%3,%4};" ::"l"(SC(row, (slot * 16 + (t >> 3)) * 16)), "f"(m), "f"(r1),
                   "f"(r1 * rsq(var * r1 * r1 + 1e-5f)), "f"(__uint_as_float(ep)) : "memory");
    __syncwarp();
    STAMPW(78);
  }
  {
    {
      {
        const float* csp = (const float*)SC(cs1, 640 * q + 8 * min(t, 79));
        float x, y;
        int n = 0;
        bool again;
#pragma unroll 1
        do {
          uint2 cp[10];
#pragma unroll
          for (int k = 0; k < 10; k++) asm volatile("ld.relaxed.gpu.global.v2.u32 {%0,%1}, [%2];" : "=r"(cp[k].x), "=r"(cp[k].y) : "l"(csp + k * 640) : "memory");
          uint32_t o = 0, a = ~0u;
          x = y = 0.f;
#pragma unroll
          for (int k = 0; k < 10; k++) { o |= cp[k].x | cp[k].y; a &= cp[k].x & cp[k].y; x += __uint_as_float(cp[k].x); y += __uint_as_float(cp[k].y); }
          again = __any_sync(~0u, ((o ^ ep) | (a ^ ep)) & 1);
        } while (again && ++n < SPIN_MAX);
        if (again) __trap();
        if (t < 80) sts_f2(CS1 + t * 8, x, y);
        __syncwarp();
        nb_arrive(NB_STATS, 416);
        STAMPW(29);
      }
      mbar_wait(B_ROW, 0);
      const float mu0 = __uint_as_float(lds_u32(ROW + r0 * 16)), mu1 = __uint_as_float(lds_u32(ROW + 128 + r0 * 16));
      mbar_wait(B_FF + 4 * 8, 0);
#pragma unroll 1
      for (int j = 0; j < (G0M ? 3 : 5); j++) {
        mbar_wait(B_EM + (j ? j - 1 : 5) * 8, j > 0);
        if (j == 2 || j == 3) mbar_wait(B_FF + (j == 2 ? 5 : 1) * 8, 0);
        if (j == 0) STAMPW(66);
        fold(b, j, srow * 128, sx, mu0, mu1, odd);
      }
      fence_async_smem();
      float acc[80];
      if (G0M) nb_sync(NB_FOLD, 384); else nb_sync(NB_WG2, 128);
      STAMPW(33);
      uint32_t s = 5, sp = 4;
#pragma unroll 1
      for (int it = 0; it < 5; it++) {
        const uint32_t a = dlo(SM, 16) + s * SL16;
        mbar_wait(B_FF + s * 8, 0);
        wg_fence();
#pragma unroll
        for (int kk = 0; kk < 4; kk++) wg_ss_160<0, H128, H128>(acc, a + 2 * kk, a + 512 + 2 * kk, kk ? 1 : it);
        wg_commit();
        wg_wait<1>();
        if (t == 0) mbar_arrive_n(B_EM + sp * 8, 2);
        sp = s; s = s == NST - 1 ? 0 : s + 1;
      }
      wg_wait<0>();
      if (t == 0) mbar_arrive_n(B_EM + 3 * 8, 2);
      pin(acc);
      STAMPW(34);
#pragma unroll
      for (int j = 0; j < 10; j++) {
        const float* a = &acc[j * 8];
        stsm4(sbase + (j >> 2) * 8192 + (sx ^ ((j & 3) << 5)), pack2(a[0], a[1]), pack2(a[2], a[3]), pack2(a[4], a[5]), pack2(a[6], a[7]));
      }
      fence_async_smem();
      nb_arrive(NB_F1, 384);
      STAMPW(76);
    }
  }
  {
    const int k1 = slot >> 1, u = 8 * w + (lane >> 2);
#pragma unroll 1
    for (int ps = 0; ps < 2; ps++) {
      uint32_t D[8];
      d_frags(D, ps ? u * k1 : 0, ps ? 64 * u : k1 + 64 * u, lane);
      sts_u4((ps ? DFR + 2048 : DF0) + t * 16, D[0], D[1], D[2], D[3]); sts_u4(DFR + ps * 4096 + t * 16, D[4], D[5], D[6], D[7]);
    }
    __syncwarp();
    if (lane == 0) mbar_arrive(B_FFT);
  }
  {
    uint32_t Cf[16], Sf[16];
    e_frags(Cf, Sf, r0, lane);
    mbar_wait(B_U, 0);
    STAMPW(42);
    s_step(Cf, Sf, 3 - odd, sbase, sx);
    STAMPW(43);
  }
  {
    float p[40], r[40];
    uint32_t s = 70 % NST;
#pragma unroll 1
    for (int j = 0; j < 5; j++) {
      const uint32_t a0 = dlo(SM, 16) + s * SL16, a1 = dlo(STG, 16) + j * 512, b0 = a0 + 512, b1 = b0 + 640;
      const uint32_t ap = j < 4 ? a0 + 4 : a1, bp = j < 4 ? b0 + 4 : b1, aq = j < 4 ? a1 : a0 + 4, bq = j < 4 ? b1 : b0 + 4;
      mbar_wait(B_FF + s * 8, 1);
      wg_fence();
      wg_ss_80<0, H128, H128>(p, a0, b0, j); wg_ss_80<0, H128, H128>(p, a0 + 2, b0 + 2, 1);
      wg_ss_80<0, H128, H128>(p, ap, bp, 1); wg_ss_80<0, H128, H128>(p, ap + 2, bp + 2, 1);
      wg_ss_80<0, H128, H128>(r, aq, bq, j); wg_ss_80<0, H128, H128>(r, aq + 2, bq + 2, 1);
      wg_ss_80<0, H128, H128>(r, a1 + 4, b1 + 4, 1); wg_ss_80<0, H128, H128>(r, a1 + 6, b1 + 6, 1);
      wg_commit();
      s = s == NST - 1 ? 0 : s + 1;
    }
    wg_wait<0>();
    nb_sync(NB_WG2, 128);
    pin(p); pin(r);
    STAMPW(45);
#pragma unroll
    for (int j = 0; j < 5; j++) {
      uint32_t o0[4], o1[4];
#pragma unroll
      for (int u = 0; u < 4; u++) {
        const int f = 8 * j + 2 * u;
        o0[u] = pack2(p[f] + r[f], p[f + 1] + r[f + 1]); o1[u] = pack2(p[f] - r[f], p[f + 1] - r[f + 1]);
      }
      stsm4(sbase + (j < 4 ? (sx ^ (j << 5)) : 16384 + sx), o0[0], o0[1], o0[2], o0[3]);
      stsm4(sbase + (j < 4 ? 8192 + (sx ^ (j << 5)) : 16384 + (sx ^ 32)), o1[0], o1[1], o1[2], o1[3]);
    }
  }
  nb_arrive(NB_S, 384);
}

DEVI void helper_role(const Params& P, int slot, int warp, uint32_t t_start) {
  const int tid = threadIdx.x, q = slot & 3;
  const int n2 = q == 3 ? 1 : 3;
  if (warp == 15) {
    uint32_t ep = 0;
    if (elect()) { bulk_st(SC(tab, 786432 + q * 8192), HTB, 8192); bulk_commit(); }
#pragma unroll 1
    for (int j = 0; j < 17; j++) {
      const int d = j == 1 ? 0 : j > 4 ? j - 4 : -1;
      if (d >= 0) nb_sync(3, 416);
      if (elect()) {
        if (d == 0 || d >= 11) { bulk_st(SC(rem, (d ? 6 * q + 3 * d - 23 : 3 * q) * 16384), SM + (d & 3) * 49152, (d ? 3 : n2) * 16384); bulk_commit(); }
        if (d == 10) { bulk_st(SC(cs3, q * 6144), HTB, 6144); bulk_commit(); }
        if (j == 4 || d == 10 || d == 12) { bulk_wait_all(); flag_add(P.sc, j == 4 ? F_W2 : d == 10 ? F_CS3 : F_W4); }
        if (j < 13) {
          const uint32_t mb = BAR + (j & 3) * 8, buf = SM + (j & 3) * 49152;
          mbar_arrive(mb); mbar_expect(mb, j ? 49152 : n2 * 16384);
          if (j == 0 || j > 10) {
#pragma unroll 1
            for (int u = 0; u < (j ? 3 : n2); u++) {
              const int t = 6 * q + 3 * (j - 11) + u;
              const int row = j ? 192 * (t & 7) + 64 * (t >> 3) : 64 * (3 * q + u);
              tma_ld2(buf + u * 16384, j ? &P.w4h : &P.w2h, mb, 256, row); tma_ld2(buf + u * 16384 + 8192, j ? &P.w4h : &P.w2h, mb, 576, row);
            }
          } else bulk_ld(buf, (const unsigned char*)P.pw3 + q * 491520 + (j - 1) * 49152, 49152, mb);
        }
        if (j == 0) { bulk_wait_all(); flag_add(P.sc, F_TAB); }
      }
      __syncwarp();
    }
    ep = ldg_u32(&P.sc->epoch[slot]) + 1;
    __syncwarp();
    if (elect()) P.sc->epoch[slot] = ep;
    flag_wait(P.sc, F_TAB, ep * 132);
    return;
  }
  if (warp >= 12) return;
  float c[8];
  zero(c);
  const uint32_t mo = ((tid >= 192 ? 7 * 192 : 0) + tid) * 16;
#pragma unroll 1
  for (int j = 0; j < 13; j++) {
    const uint32_t buf = SM + (j & 3) * 49152;
    mbar_wait(BAR + (j & 3) * 8, (j >> 2) & 1);
    if (j == 0 || j > 10) {
      const uint32_t bs = buf + (tid >> 7) * 16384;
      const int k0 = (tid & 127) >> 3, cc = tid & 7;
      uint4 v[8];
#pragma unroll
      for (int u = 0; u < 8; u++) v[u] = lds_u4(bs + (u & 1) * 8192 + sw128(k0 + 16 * (u >> 1), cc));
      landed(v[0].x ^ v[1].x ^ v[2].x ^ v[3].x ^ v[4].x ^ v[5].x ^ v[6].x ^ v[7].x);
      nb_sync(5, 384);
#pragma unroll
      for (int u = 0; u < 8; u++)
        sts_u4(bs + (cc >> 1) * 4096 + sw128(k0 + 16 * ((u >> 1) & 1), (u >> 2) * 4 + 2 * (u & 1) + (cc & 1)), v[u].x, v[u].y, v[u].z, v[u].w);
    } else {
#pragma unroll
      for (int i = 0; i < 8; i++) acc8(c, lds_u4(buf + mo + i * 3072));
      landed(__float_as_uint(c[0]));
      if (j == 10) {
        if (tid >= 192) { sts_f4(HTB + (tid - 192) * 32, c[0], c[1], c[2], c[3]); sts_f4(HTB + (tid - 192) * 32 + 16, c[4], c[5], c[6], c[7]); }
        nb_sync(5, 384);
        if (tid < 192) {
          const float4 a = lds_f4(HTB + tid * 32), d = lds_f4(HTB + tid * 32 + 16);
          sts_f4(HTB + tid * 32, c[0] + a.x, c[1] + a.y, c[2] + a.z, c[3] + a.w); sts_f4(HTB + tid * 32 + 16, c[4] + d.x, c[5] + d.y, c[6] + d.z, c[7] + d.w);
        }
      }
    }
    fence_async_smem();
    nb_sync(3, 416);
  }
}

DEVI void l2_trickle(const void* p, int n, int slot, int lane) {
  const char* a = (const char*)p + (uint32_t)(slot * n);
#pragma unroll 1
  for (int o = 0; o < n; o += 4096) { asm volatile("prefetch.global.L2 [%0];" ::"l"(a + (uint32_t)min(o + lane * 128, n - 1))); __nanosleep(100); }
}

template <int I0, int I1> DEVI void init_barriers() {
#pragma unroll
  for (int i = I0; i < I1; i++) mbar_init(BAR + i * 8, BAR + i * 8 < B_G1 ? 2 : BAR + i * 8 == B_CSR ? 3 : BAR + i * 8 == B_FFT ? 5 : BAR + i * 8 >= B_H2 ? 8 : 1);
  asm volatile("fence.mbarrier_init.release.cluster;" ::: "memory");
}

__global__ void __launch_bounds__(512, 1) fused_kernel(const __grid_constant__ Params P) {
  extern __shared__ __align__(1024) unsigned char smem_raw[];
  const int tid = threadIdx.x, lane = tid & 31;
  const int warp = __shfl_sync(~0u, tid >> 5, 0);
  const uint32_t t_start = 0;
  uint32_t nsm, smid;
  asm volatile("mov.u32 %0, %%nsmid;" : "=r"(nsm));
  asm volatile("mov.u32 %0, %%smid;" : "=r"(smid));
  const int ts = P.slot[min(smid, 131u)], slot = nsm == 132 ? ts : blockIdx.x;
  const int b = slot >> 2, q = slot & 3, odd = q & 1;

  const int blkA = (5 * q + 1) >> 1, colS = 160 * q + (odd ? 0 : 128);
  if (warp == 14 && elect()) { tmap_pf(&P.x); tmap_pf(&P.w1a); tmap_pf(&P.w1b); }
  if (warp == 12 && slot < 128) {
    STAMP(24);
    if (elect()) init_barriers<0, NPRE>();
    __syncwarp();
    nb_arrive(NB_GO, 448);
    if (elect()) {
#pragma unroll 1
      for (int it = 0; it < NPRE; it++) {
        const uint32_t dst = SM + it * SLOT, fb = B_FM + it * 8;
        mbar_arrive(fb); mbar_expect(fb, 28672);
        const int k0 = g1_chunk(b, it) * 64;
        tma_ld3(dst, &P.x, fb, k0, b, 0);
        tma_ld3(dst + 8192, &P.w1a, fb, 0, k0, blkA); tma_ld2(dst + 24576, &P.w1b, fb, colS, k0); tma_ld2(FB + it * 4096, &P.w1b, fb, colS, k0 + 32);
      }
    }
    __syncwarp();
    STAMP(72);
  }
  if (warp == 13 && slot < 128) {
    if (elect()) init_barriers<NPRE, NBAR>();
    __syncwarp();
    nb_arrive(NB_GO, 448); nb_arrive(NB_EP, 64);
    STAMP(46);
  }
  if (warp < 12 || slot >= 128) {
    {
      const int g = slot < 128 ? slot * 384 + tid : 49152 + (slot - 128) * 512 + tid;
      const int inv = g >= 25600, R = (g - (inv ? 25600 : 0)) >> 3;
      const int tq = R / 800, Rq = R - 800 * tq;
      const int kc = inv ? Rq / 80 : Rq / 160, r = Rq - kc * (inv ? 80 : 160);
      const int k0 = 64 * kc + 8 * ((g & 7) ^ (r & 7));
      const int rr = (tq & 1) ? (r >= 128 ? r - 128 : r + 32) : r;
      const int kq = k0 / 160;
      const int mf = 160 * (tq >> 1) + (rr & ~1) + (tq & 1), m = mf ? mf : 320;
      const int d = r < 64 ? 64 * tq + r : 192 + 16 * tq + r;
      const int m2 = 160 * (kq >> 1) + (k0 - 160 * kq) + (kq & 1) + 4;
      int S = 2 * (inv ? d : m);
      const int base = ((inv ? m2 * d : (k0 + 4) * m + (rr & 1) * 160) + 320) % 640 - 320;
      S -= S > 320 ? 640 : 0;
      const float bs = (float)base, Sf = (float)S, H = inv ? 160.f : (float)m;
      uint32_t v[4];
#pragma unroll
      for (int e = 0; e < 4; e++) {
        float lo = fmaf((float)(e - 2), Sf, bs);
        if (e == 0 && inv && k0 == 0) lo = (float)((d & 1) * 320);
        v[e] = pack2(__cosf(lo * 0.009817477042468103f), __cosf((lo + H) * 0.009817477042468103f));
      }
      sts_u4((slot < 128 ? STG : HTB) + tid * 16, v[0], v[1], v[2], v[3]);
      STAMP(27);
      fence_async_smem();
    }
  }
  if (warp < 12 || slot >= 128) {
    if (slot >= 128) {
      if (tid == 0) init_barriers<0, 8>();
      __syncthreads();
      helper_role(P, slot, warp, t_start);
    } else {
      nb_sync(NB_GO, 448);
      nb_arrive(NB_TAB, 416);
      if (warp == 0) STAMP(0);
      if (warp >= 4) {
        asm volatile("setmaxnreg.inc.sync.aligned.u32 176;");
        mlp_role(P, b, q, warp >> 3, warp & 3, t_start);
      } else {
        asm volatile("setmaxnreg.inc.sync.aligned.u32 136;");
        fft_role(P, slot, warp & 3, t_start);
      }
    }
  } else {
    asm volatile("setmaxnreg.dec.sync.aligned.u32 24;");
    uint32_t s = NPRE, ph = 1;
#define PSTEP(FULL_, bytes, ISSUE) { mbar_wait(B_EM + s * 8, ph); const uint32_t dst = SM + s * SLOT, fb = FULL_ + s * 8; \
      if (elect()) { mbar_expect(fb, bytes); ISSUE; } __syncwarp(); if (++s == NST) { s = 0; ph ^= 1; } }
    if (warp == 14) {
      STAMP(49);
      nb_sync(NB_TAB, 416);
      if (elect()) { bulk_st(SC(tab, slot * 6144), STG, 6144); bulk_commit(); bulk_wait_all(); flag_add(P.sc, F_TAB); }
      __syncwarp();
      STAMP(64);
      mbar_wait(B_EP, 0);
      const uint32_t ep = lds_u32(EPO);
      {
        float4 v, u;
        int n = 0;
        bool ok;
        const unsigned char* rp = SC(row, (b * 64 + lane) * 16);
#pragma unroll 1
        do {
          asm volatile("ld.relaxed.gpu.global.v4.f32 {%0,%1,%2,%3}, [%4];" : "=f"(v.x), "=f"(v.y), "=f"(v.z), "=f"(v.w) : "l"(rp) : "memory");
          asm volatile("ld.relaxed.gpu.global.v4.f32 {%0,%1,%2,%3}, [%4+512];" : "=f"(u.x), "=f"(u.y), "=f"(u.z), "=f"(u.w) : "l"(rp) : "memory");
          ok = __all_sync(~0u, __float_as_uint(v.w) == ep && __float_as_uint(u.w) == ep);
        } while (!ok && ++n < SPIN_MAX);
        if (!ok) __trap();
        sts_f4(ROW + lane * 16, v.x, v.y, v.z, v.w); sts_f4(ROW + 512 + lane * 16, u.x, u.y, u.z, u.w);
      }
      __syncwarp();
      if (elect()) mbar_arrive(B_ROW);
      STAMP(31);
      nb_arrive(NB_STATS, 416);
      l2_trickle(P.pw2, 6400, slot, lane);
#pragma unroll 1
      for (int jb = 0; jb < 2; jb++) {
        const int bd = (b + (q & 2 ? 2 : 1) * (odd ? -1 : 1)) & 31;
        unsigned char* d = keep(SC(h, (jb ? 2621440 + b * 81920 : bd * 81920) + q * 20480));
        mbar_wait(B_H2, jb);
        if (elect()) {
          bulk_st(d, STG, 20480);
          bulk_commit();
          if (jb == 0) {
            bulk_wait_read();
            mbar_expect(B_CS, 22528);
            const int x0 = ((slot >> 1) * 321 + 160 * (slot & 1)) & ~15;
            tma_ld2(STG, &P.wr, B_CS, x0, 0); tma_ld2(STG + 11264, &P.wi, B_CS, x0, 0);
          }
          bulk_wait_all();
          flag_add(P.sc, jb ? F_X1 + (b >> 2) : F_H + (bd >> 2));
        }
        __syncwarp();
        STAMP(58 + jb);
        if (jb) {
          nb_sync(NB_RDY, 288);
          if (elect()) { bulk_st(SC(st1, slot * 1024), ST1, 1024); bulk_commit(); bulk_wait_all(); flag_add(P.sc, F_ST + (b >> 1)); }
          __syncwarp();
        }
        if (jb == 0) { mbar_wait(B_CS, 0); l2_trickle(P.pw4, 15360, slot, lane); }
      }
      flag_wait(P.sc, F_ST + (b >> 1), ep * 8);
      flag_wait(P.sc, F_CS3, ep * 4);
      mbar_wait(B_G1, 1);
      if (elect()) {
        mbar_expect(B_CS, 3072 + 8192);
        bulk_ld(STP, SC(st1, (b & ~1) * 4096), 8192, B_CS);
#pragma unroll 1
        for (int u = 0; u < 4; u++) bulk_ld(CSP + u * 768, SC(cs3, u * 6144 + (2 * q + (b & 1)) * 768), 768, B_CS);
      }
      mbar_wait(B_CS, 1);
#pragma unroll 1
      for (int i0 = 0; i0 < 768; i0 += 256) {
        const int i = i0 + lane * 8;
        const float2 a = lds_f2(CSP + i), c = lds_f2(CSP + 768 + i), d = lds_f2(CSP + 1536 + i), f = lds_f2(CSP + 2304 + i);
        sts_f2(CS3 + i, (a.x + c.x) + (d.x + f.x), (a.y + c.y) + (d.y + f.y));
      }
      STAMP(30);
      __syncwarp();
      if (elect()) mbar_arrive(B_ROW);
      __syncwarp();
      watch(P.sc, F_W4, ep * 4, 2);
#pragma unroll 1
      for (int j = 0; j < 6; j++) {
        unsigned char* d = keep(SC(h2, (b & ~1) * 196608 + (j >> 1) * 65536 + (2 * q + (b & 1)) * 8192 + (j & 1) * 4096));
        mbar_wait(B_H2 + j * 8, 0);
        if (elect()) {
          bulk_st(d, STG + j * 8192, 4096); bulk_st(d + 196608, STG + j * 8192 + 4096, 4096);
          bulk_commit();
          if (j == FLAGA) { asm volatile("cp.async.bulk.wait_group %0;" ::"n"(FLAGA - 1) : "memory"); flag_add(P.sc, F_H2 + (b >> 2)); }
        }
        __syncwarp();
        if (j == 0) STAMP(79);
        if (j == FLAGA) STAMP(60);
      }
      if (elect()) { bulk_wait_all(); flag_add(P.sc, F_H2 + 8 + (b >> 2)); }
      __syncwarp();
      STAMP(62);
      watch(P.sc, F_H2 + 8 + (b >> 2), ep * 16, 3);
      nb_sync(NB_RDY, 288);
      if (elect()) {
        tma_st4(&P.outa, STG, 64 * q, 0, 0, b); tma_st4(&P.outr, STG + 16384, 256 + 16 * q, 0, 0, b);
        bulk_commit(); bulk_wait_read();
      }
      __syncwarp();
      STAMP(63);
    } else if (warp == 15) {
      if ((uint32_t)__cvta_generic_to_shared(smem_raw) != SM) __trap();
      const uint32_t ep = ldg_u32(SC(epoch, slot * 4)) + 1;
      nb_sync(NB_EP, 64);
      if (elect()) { *(uint32_t*)SC(epoch, slot * 4) = ep; sts_u32(EPO, ep); mbar_arrive(B_EP); }
      __syncwarp();
      STAMP(74);
#pragma unroll 1
      for (int i = 3; i < 15; i++) tmap_pf(&P.x + i);
      watch(P.sc, F_TAB, ep * 132, 0);
      mbar_wait(B_FM + 5 * 8, 0);
#pragma unroll 1
      for (int a = 0; a < 3; a++) l2_trickle(a == 2 ? P.pw3 : a ? P.pwi : P.pwr, a == 2 ? 15360 : 10272, slot, lane);
      STAMP(28);
      watch(P.sc, F_W2, ep * 4, 1);
      const int k1 = slot >> 1, hh = slot & 1;
      nb_sync(NB_T2, 288);
      if (elect()) {
        tma_st4(&P.t1h, FB + 16384, 0, 0, 5 * q + (odd ? 0 : 4), b);
#pragma unroll 1
        for (int i = 0; i < 4; i++) {
          const uint32_t t0 = (uint32_t)clock64();
          while (i >= T1FREE && (uint32_t)clock64() - t0 < T1GAP) {}
          tma_st4(&P.t1a, FB + i * 4096, 0, 32 * (i & 1), blkA + (i >> 1), b);
        }
        bulk_commit();
        bulk_wait_all(); flag_add(P.sc, F_T1 + (q >> 1));
      }
      __syncwarp();
      STAMP(75);
      flag_wait(P.sc, F_T1 + hh, ep * 64);
      STAMP(37);
      if (elect()) { mbar_expect(B_FFT, 20480); tma_ld3(FB, &P.t1l, B_FFT, 0, k1 * 32, 5 * hh); }
      nb_sync(NB_T2, 288);
      if (elect()) { tma_st4(&P.t2s, FB, 0, 0, 5 * hh, k1); bulk_commit(); bulk_wait_all(); flag_add(P.sc, F_T2 + hh); mbar_arrive(B_G1); }
      __syncwarp();
      STAMP(40);
      flag_wait(P.sc, F_T2 + (q >> 1), ep * 64);
      STAMP(41);
      if (elect()) {
        mbar_expect(B_U, (3 - odd) * 8192);
#pragma unroll 1
        for (int i = 0; i < 3 - odd; i++) tma_ld2(FB + i * 8192, &P.t2l, B_U, (blkA + i) * 64, b * 64);
      }
      unsigned char* yd = keep(SC(Y, (b * 10 + blkA) * 8192));
      nb_sync(NB_DMA, 160);
      if (elect()) { bulk_st(yd, FB, (3 - odd) * 8192); bulk_commit(); bulk_wait_all(); flag_add(P.sc, F_Y + (b >> 2)); mbar_arrive(B_YD); }
      __syncwarp();
      STAMP(44);
      watch(P.sc, F_Y + (b >> 2), ep * 16, 4);
      STAMP(54);
    } else if (warp == 13) {
      nb_sync(NB_INIT, 64);
#pragma unroll 1
      for (int it = NPRE; it < 10; it++) PSTEP(B_FM, 8192, tma_ld3(dst, &P.x, fb, g1_chunk(b, it) * 64, b, 0));
      PSTEP(B_FF, 16384, mbar_arrive(fb); tma_ld3(dst + 8192, &P.x, fb, g1_chunk(b, 0) * 64, b, 0); tma_ld3(dst + 16384, &P.x, fb, g1_chunk(b, 1) * 64, b, 0));
#pragma unroll 1
      for (int it = 0; it < 5; it++)
        PSTEP(B_FF, (it & 5) ? 0 : 8192, (void)dst; if (!(it & 5)) tma_ld3(FB + (s - 1) * 4096, &P.x, fb, g1_chunk(b, 2 + (it >> 1)) * 64, b, 0));
      mbar_wait(B_EP, 0);
      const uint32_t ep = lds_u32(EPO);
#pragma unroll 1
      for (int g = 0; g < 3; g++) {
        const unsigned char* src = SC(h, g == 0 ? b * 81920 : g == 1 ? 2621440 + (b & ~1) * 81920 : 5242880 + b * 196608);
        const int n = g == 0 ? 10 : g == 1 ? 20 : 24, step = g == 1 ? 4096 : 8192, o2 = g == 1 ? 81920 : 4096;
        flag_wait4(P.sc, F_H + 8 * g + (b >> 2), ep * 16);
        if (g == 0 && elect()) mbar_arrive(B_G1);
        __syncwarp();
        STAMP(g == 2 ? 55 : 52 + g);
#pragma unroll 1
        for (int it = 0; it < n; it++) {
          if (g == 2 && it == 8) watched(3);
          PSTEP(B_FM, 8192, bulk_ld(dst, src, 4096, fb); bulk_ld(dst + 4096, src + o2, 4096, fb));
          src += step;
        }
      }
      const unsigned char* src = SC(Y, b * 81920);
      watched(4);
#pragma unroll 1
      for (int it = 0; it < 5; it++) PSTEP(B_FF, 16384, bulk_ld(dst, src + G5C(it) * 8192, 8192, fb); bulk_ld(STG + it * 8192, src + (G5C(it) + (it < 4 ? 3 : 5)) * 8192, 8192, fb));
    } else {
      nb_sync(NB_INIT, 64);
#pragma unroll 1
      for (int it = NPRE; it < 10; it++) {
        const int k0 = g1_chunk(b, it) * 64;
        if (it == NST) mbar_wait(B_CSR, 0);
        PSTEP(B_FM, 20480, tma_ld3(dst + 8192, &P.w1a, fb, 0, k0, blkA); tma_ld2(dst + 24576, &P.w1b, fb, colS, k0); tma_ld2(FB + s * 4096, &P.w1b, fb, colS, k0 + 32));
        if (it == 5) STAMP(73);
      }
      s = 5;
#pragma unroll 1
      for (int g = 0; g < 2; g++) {
        if (g == 0) watched(0);
        else {
#pragma unroll 1
          for (int m = 0; m < 2; m++) {
            watched(1 + m);
            if (m == 0) mbar_wait(B_G1, 0);
            const unsigned char* rem = SC(rem, q * 4096 + m * 163840);
#pragma unroll 1
            for (int it = 0; it < (m ? 24 : 10); it++) {
              PSTEP(B_FM, 20480, tma_ld3(dst + 8192, &P.w2a + m, fb, 64 * q, m ? 192 * (it & 7) + 64 * (it >> 3) : 64 * it, 0); bulk_ld(dst + 24576, rem, 4096, fb));
              rem += 16384;
            }
#pragma unroll 1
            for (int it = 0; it < (m ? 0 : 20); it++) {
              const int gr = it / 5, j = it - 5 * gr;
              PSTEP(B_FM, 12288, tma_ld4(dst + 8192, &P.w3, fb, 0, j < 4 ? 64 * gr + 16 * j : 256 + 16 * gr, 6 * q + 3 * (b & 1), 0));
            }
          }
        }
#pragma unroll 1
        for (int it = 0; it < 5; it++) {
          const int c = g1_chunk(b, it);
          const unsigned char* tp = SC(tab, q * 102400 + (g ? 40 + G5C(it) : c >= 5 ? 2 * c - 10 : 2 * c) * 10240);
          PSTEP(B_FF, 20480, bulk_ld(dst + 8192, tp, 10240, fb); bulk_ld(dst + 18432, tp + (g ? (it < 4 ? 3 : 5) : 1) * 10240, 10240, fb));
        }
      }
    }
#undef PSTEP
  }
}

typedef CUresult (*EncFn)(CUtensorMap*, CUtensorMapDataType, cuuint32_t, void*, const cuuint64_t*, const cuuint64_t*, const cuuint32_t*,
                          const cuuint32_t*, CUtensorMapInterleave, CUtensorMapSwizzle, CUtensorMapL2promotion, CUtensorMapFloatOOBfill);

static void enc(EncFn fn, CUtensorMap* m, const void* p, int rank, const cuuint64_t* dims, const cuuint64_t* strides, const cuuint32_t* box, int sw) {
  cuuint32_t es[5] = {1, 1, 1, 1, 1};
  fn(m, CU_TENSOR_MAP_DATA_TYPE_BFLOAT16, rank, (void*)p, dims, strides, box, es, CU_TENSOR_MAP_INTERLEAVE_NONE,
     sw == 128 ? CU_TENSOR_MAP_SWIZZLE_128B : sw == 32 ? CU_TENSOR_MAP_SWIZZLE_32B : CU_TENSOR_MAP_SWIZZLE_NONE, CU_TENSOR_MAP_L2_PROMOTION_L2_128B,
     CU_TENSOR_MAP_FLOAT_OOB_FILL_NONE);
}

extern "C" void kernel_launch(void* const* d_in, const int* in_sizes, int n_in, void* d_out, int out_size) {
  (void)in_sizes; (void)n_in; (void)out_size;
  void* fnp = nullptr;
  cudaDriverEntryPointQueryResult qr;
  cudaGetDriverEntryPoint("cuTensorMapEncodeTiled", &fnp, cudaEnableDefault, &qr);
  EncFn fn = (EncFn)fnp;
  Scratch* sc;
  cudaGetSymbolAddress((void**)&sc, g_sc);
  void *t1 = sc->T1, *t2 = sc->T2;

  Params P;
  P.sc = sc;
  P.px = (const __nv_bfloat16*)d_in[0]; P.pwr = (const __nv_bfloat16*)d_in[1]; P.pwi = (const __nv_bfloat16*)d_in[2];
  P.pw1 = (const __nv_bfloat16*)d_in[4]; P.pw2 = (const __nv_bfloat16*)d_in[5]; P.pw3 = (const __nv_bfloat16*)d_in[6]; P.pw4 = (const __nv_bfloat16*)d_in[7];
  { cuuint64_t d[3] = {640, 32, 64}, s[2] = {1280, 40960}; cuuint32_t bx[3] = {64, 1, 64}; enc(fn, &P.x, d_in[0], 3, d, s, bx, 128); }
  { cuuint64_t d[3] = {64, 640, 10}, s[2] = {1280, 128}; cuuint32_t bx[3] = {64, 64, 2}; enc(fn, &P.w1a, d_in[4], 3, d, s, bx, 128); }
  { cuuint64_t d[2] = {640, 640}, s[1] = {1280}; cuuint32_t bx[2] = {32, 32}; enc(fn, &P.w1b, d_in[4], 2, d, s, bx, 128); }
  { cuuint64_t d[3] = {320, 1536, 2}, s[2] = {1280, 640}; cuuint32_t bx[3] = {64, 64, 2}; enc(fn, &P.w4a, d_in[7], 3, d, s, bx, 128);
    d[1] = 640; enc(fn, &P.w2a, d_in[5], 3, d, s, bx, 128); }
  { cuuint64_t d[2] = {640, 640}, s[1] = {1280}; cuuint32_t bx[2] = {64, 64}; enc(fn, &P.w2h, d_in[5], 2, d, s, bx, 128); }
  { cuuint64_t d[2] = {640, 1536}, s[1] = {1280}; cuuint32_t bx[2] = {64, 64}; enc(fn, &P.w4h, d_in[7], 2, d, s, bx, 128); }
  { cuuint64_t d[2] = {20544, 32}, s[1] = {41088}; cuuint32_t bx[2] = {176, 32}; enc(fn, &P.wr, d_in[1], 2, d, s, bx, 0); enc(fn, &P.wi, d_in[2], 2, d, s, bx, 0); }
  { cuuint64_t d[4] = {64, 320, 24, 2}, s[3] = {3072, 128, 983040}; cuuint32_t bx[4] = {64, 16, 3, 2}; enc(fn, &P.w3, d_in[6], 4, d, s, bx, 128); }
  { cuuint64_t d[4] = {64, 64, 10, 32}, s[3] = {40960, 128, 1280}; cuuint32_t bx[4] = {64, 32, 1, 1}; enc(fn, &P.t1a, t1, 4, d, s, bx, 128); }
  { cuuint64_t d[4] = {32, 64, 20, 32}, s[3] = {40960, 64, 1280}; cuuint32_t bx[4] = {64, 64, 1, 1}; enc(fn, &P.t1h, t1, 4, d, s, bx, 128); }
  { cuuint64_t d[3] = {64, 2048, 10}, s[2] = {1280, 128}; cuuint32_t bx[3] = {64, 32, 5}; enc(fn, &P.t1l, t1, 3, d, s, bx, 128); }
  { cuuint64_t d[4] = {64, 32, 10, 64}, s[3] = {81920, 128, 1280}; cuuint32_t bx[4] = {64, 32, 5, 1}; enc(fn, &P.t2s, t2, 4, d, s, bx, 128); }
  { cuuint64_t d[2] = {640, 2048}, s[1] = {1280}; cuuint32_t bx[2] = {64, 64}; enc(fn, &P.t2l, t2, 2, d, s, bx, 128); }
  { cuuint64_t d[4] = {320, 64, 2, 32}, s[3] = {40960, 640, 1280}; cuuint32_t ba[4] = {64, 64, 2, 1}, br[4] = {16, 64, 2, 1};
    enc(fn, &P.outa, d_out, 4, d, s, ba, 128); enc(fn, &P.outr, d_out, 4, d, s, br, 32); }

  for (int i = 0; i < 132; i++) {
    const int u = i - 64;
    P.slot[i] = i < 64 ? ((i >> 1) & 7) * 16 + (i >> 4) * 2 + (i & 1) : i < 120 ? (1 + (u >> 1) % 7) * 16 + 8 + (u / 14) * 2 + (u & 1) : i < 124 ? i + 8 : i - 116;
    if (P.slot[i] < 128) { const int j = P.slot[i] & 15; P.slot[i] = (P.slot[i] & ~15) + 4 * (2 * (j & 1) + (j >> 3)) + ((j >> 1) & 3); }
  }
  cudaFuncSetAttribute(fused_kernel, cudaFuncAttributeMaxDynamicSharedMemorySize, SMEM_BYTES);
  fused_kernel<<<132, 512, SMEM_BYTES>>>(P);
}
```
